```python
import torch

def _softmax(x, axis=-1):
    return torch.softmax(x, dim=axis)
def _gelu(x):
    return torch.nn.functional.gelu(x, approximate="tanh")
def _silu(x):
    return torch.nn.functional.silu(x)
def _sigmoid(x):
    return torch.sigmoid(x)
def _layernorm(x, axis=-1, eps=1e-5):
    m = x.mean(dim=axis, keepdim=True)
    v = x.var(dim=axis, keepdim=True, unbiased=False)
    return (x - m) / torch.sqrt(v + eps)
def _scatter_add(tgt, idx, src, axis=0):
    return tgt.clone().index_add_(axis, idx, src)
def _segment_sum(src, seg, n):
    out = torch.zeros((n,) + src.shape[1:], dtype=src.dtype)
    return out.index_add_(0, seg, src)
def _pad(x, pw):
    flat = tuple(v for pair in reversed(pw) for v in pair)
    return torch.nn.functional.pad(x, flat)

kernel_name = 'recurrent_scan__ssm_conv_s4d__mixer_channel_mlp__prompt'

def setup_inputs():

    _w = (lambda a: (lambda t: t.to(torch.bfloat16) if t.is_floating_point() else t)(torch.as_tensor(a)))
    def _A_setup():
        Bsz, L, D, N = 1, 2048, 640, 128
        return {
            "u": _w((lambda *s: torch.randn(*s, dtype=torch.bfloat16) * 0.05)(Bsz, L, D)),
            "log_A_real": _w((lambda *s: torch.randn(*s, dtype=torch.bfloat16) * 3.2)(D, N) * 0.5),
            "A_imag": _w((lambda *s: torch.randn(*s, dtype=torch.bfloat16) * 0.2)(D, N) * 3.14),
            "C_real": _w((lambda *s: torch.randn(*s, dtype=torch.bfloat16) * 0.8)(D, N) / N ** 0.5),
            "C_imag": _w((lambda *s: torch.randn(*s, dtype=torch.bfloat16) * 0.8)(D, N) / N ** 0.5),
            "log_dt": _w((lambda *s: torch.randn(*s, dtype=torch.bfloat16) * 0.2)(D) * 0.5 - 4.0),
            "D_skip": _w((lambda *s: torch.randn(*s, dtype=torch.bfloat16) * 0.2)(D)),
        }
    _A_in = _A_setup()

    def _B_setup():
        B, S, D, F = 1, 2048, 640, 1728
        return {
            "x": _w((lambda *s: torch.randn(*s, dtype=torch.bfloat16) * 0.05)(B, S, D)),
            "w1": _w((lambda *s: torch.randn(*s, dtype=torch.bfloat16) * 1.6)(D, F) * (D ** -0.5)),
            "b1": _w((lambda *s: torch.randn(*s, dtype=torch.bfloat16) * 0.8)(F)),
            "w2": _w((lambda *s: torch.randn(*s, dtype=torch.bfloat16) * 0.1)(F, D) * (F ** -0.5)),
            "b2": _w((lambda *s: torch.randn(*s, dtype=torch.bfloat16) * 0.1)(D)),
        }
    _B_in = _B_setup()

    return {
        "A_u": _A_in["u"],
        "A_log_A_real": _A_in["log_A_real"],
        "A_A_imag": _A_in["A_imag"],
        "A_C_real": _A_in["C_real"],
        "A_C_imag": _A_in["C_imag"],
        "A_log_dt": _A_in["log_dt"],
        "A_D_skip": _A_in["D_skip"],
        "B_x": _B_in["x"],
        "B_w1": _B_in["w1"],
        "B_b1": _B_in["b1"],
        "B_w2": _B_in["w2"],
        "B_b2": _B_in["b2"],
    }

def reference(A_u, A_log_A_real, A_A_imag, A_C_real, A_C_imag, A_log_dt, A_D_skip, B_x, B_w1, B_b1, B_w2, B_b2):
    def _A_ref(u, log_A_real, A_imag, C_real, C_imag, log_dt, D_skip):
        L = u.shape[1]
        dt = torch.exp(log_dt)
        A = -torch.exp(log_A_real) + 1j * A_imag
        C = (C_real + 1j * C_imag) * dt[:, None]
        pos = (lambda x, dt: x.to(dt))(torch.arange(L), log_dt.dtype)
        P = torch.exp((A * dt[:, None])[:, :, None] * pos[None, None, :])
        K = 2.0 * torch.einsum("dn,dnl->dl", C, P).real
        L2 = 2 * L
        u_t = (lambda x, *d: x.permute(*d))(u, 0, 2, 1)
        Kf = (lambda x, *a, **k: torch.fft.rfft(x.float(), *a, **k))(K, L2)
        Uf = (lambda x, *a, **k: torch.fft.rfft(x.float(), *a, **k))(u_t, L2)
        y = (lambda x, *a, **k: torch.fft.irfft(x, *a, **k).to(torch.bfloat16))(Uf * Kf[None, :, :], L2)[:, :, :L]
        y = (lambda x, *d: x.permute(*d))(y, 0, 2, 1)
        return y + u * D_skip[None, None, :]

    def _B_ref(x, w1, b1, w2, b2):
        y = _layernorm(x, axis=-1)
        h = _gelu(torch.einsum("bsd,df->bsf", y, w1) + b1)
        return torch.einsum("bsf,fd->bsd", h, w2) + b2

    x = A_u
    xn = _layernorm(x, axis=-1)
    s = _A_ref(xn, A_log_A_real, A_A_imag, A_C_real, A_C_imag, A_log_dt, A_D_skip)
    g = _silu(_B_ref(xn, B_w1, B_b1, B_w2, B_b2))
    return x + s * g
```

```cpp
#include <cuda_runtime.h>
#include <cuda_bf16.h>
#include <cuda_fp16.h>
#include <cuda.h>
#include <stdint.h>

namespace {

constexpr int L = 2048, D = 640, F = 1728;
constexpr long long SPIN_CLKS = 300000000LL;

__device__ __half         g_xnT[D * L];
__device__ __nv_bfloat16  g_h[L * F];
__device__ __nv_bfloat16  g_ycT[D * L];
__device__ float4         g_stats[L];
__device__ float          g_cs[16 * F];
__device__ unsigned       g_cnt[64 * 32];
__device__ unsigned       g_epoch[128];
#define TLREC(slot) do {} while (0)
constexpr int CNT_PREP = 0, CNT_H = 1  , CNT_CONV = 40  ;

constexpr int S1_STAGE = 45056, S1_B = 16384;
constexpr int S2_B = 0, S2_BSZ = 20480, S2_A = 81920, S2_ASZ = 16384;
constexpr int HST = 81920, HST_WG = 27648;
constexpr int AUX = 137216;
constexpr int KA = AUX, KA_SZ = 4416, KA_C1 = 2208;
constexpr int UB = KA + 5 * KA_SZ, UB_SZ = 17792;
constexpr int U_U = 0, U_P = 656, U_V5 = 5248, U_V3 = 8320, U_V9 = 11392, U_V7 = 13568, U_HS = 1088, U_P2 = 15744;
constexpr int Y4 = UB + 2 * UB_SZ, Y8 = Y4 + 6544, OST = Y8 + 4368 + 32;
constexpr int PRM = OST + 8192;
constexpr int AUX_END = PRM + 5120;
constexpr int LNT = UB, LNT_P = 1296, CSS = UB + 20736;
constexpr int TBA = UB, TBB = TBA + 2048, TB2 = TBB + 2048, TB3 = TB2 + 2048, PS = TB3 + 4096, PS_W = 2576, PS_SZ = 4 * PS_W;
constexpr int XT = AUX, YC = XT + 20480, XCH = YC + 20480;
constexpr int MISC = AUX + 81920;
constexpr int CSB = MISC, RST = CSB + 1728, EP2 = RST + 2048, SCL = EP2 + 640, BAR = SCL + 256;
constexpr int SMEM_TOTAL = BAR + 256;
static_assert(AUX_END <= MISC, "aux overflow");
static_assert(PS + 2 * PS_SZ <= PRM, "kgen overflow");
static_assert(OST % 128 == 0 && UB % 16 == 0 && Y4 % 16 == 0 && Y8 % 16 == 0 && PRM % 16 == 0, "align");
static_assert(SMEM_TOTAL <= 232448, "smem");
enum { B_FULL1 = 0, B_FULLA = 3, B_FULLB = 6, B_PRM = 10, B_EPI1 = 11, B_C8 = 12, B_PEER = 13, B_XFULL = 14, B_XCH = 15 };
constexpr int REL = BAR + 128;

__device__ __forceinline__ uint32_t smem_u32(const void* p) { return (uint32_t)__cvta_generic_to_shared(p); }
__device__ __forceinline__ void mbar_init(uint32_t b, int c) { asm volatile("mbarrier.init.shared::cta.b64 [%0], %1;" ::"r"(b), "r"(c)); }
__device__ __forceinline__ void mbar_expect(uint32_t b, uint32_t bytes) { asm volatile("mbarrier.arrive.expect_tx.shared::cta.b64 _, [%0], %1;" ::"r"(b), "r"(bytes) : "memory"); }
__device__ __forceinline__ void mbar_arrive(uint32_t b) { asm volatile("mbarrier.arrive.shared::cta.b64 _, [%0];" ::"r"(b) : "memory"); }
__device__ __forceinline__ uint32_t mapa(uint32_t a, uint32_t cta) { uint32_t r; asm volatile("mapa.shared::cluster.u32 %0, %1, %2;" : "=r"(r) : "r"(a), "r"(cta)); return r; }
__device__ __forceinline__ void mbar_arrive_cluster(uint32_t ra) { asm volatile("mbarrier.arrive.release.cluster.shared::cluster.b64 _, [%0];" ::"r"(ra) : "memory"); }
__device__ __forceinline__ bool mbar_try(uint32_t b, uint32_t ph) {
  uint32_t ok;
  asm volatile("{\n.reg .pred p;\nmbarrier.try_wait.parity.shared::cta.b64 p, [%1], %2;\nselp.u32 %0,1,0,p;\n}" : "=r"(ok) : "r"(b), "r"(ph) : "memory");
  return ok;
}
__device__ __forceinline__ void mbar_wait(uint32_t b, uint32_t ph) {
  if (mbar_try(b, ph)) return;
  long long t0 = clock64();
  while (!mbar_try(b, ph)) { if (clock64() - t0 > SPIN_CLKS) __trap(); }
}
__device__ __forceinline__ bool mbar_try_cl(uint32_t b, uint32_t ph) {
  uint32_t ok;
  asm volatile("{\n.reg .pred p;\nmbarrier.try_wait.parity.acquire.cluster.shared::cta.b64 p, [%1], %2;\nselp.u32 %0,1,0,p;\n}" : "=r"(ok) : "r"(b), "r"(ph) : "memory");
  return ok;
}
__device__ __forceinline__ void mbar_wait_cl(uint32_t b, uint32_t ph) {
  if (mbar_try_cl(b, ph)) return;
  long long t0 = clock64();
  while (!mbar_try_cl(b, ph)) { if (clock64() - t0 > SPIN_CLKS) __trap(); }
}
#define bar_sync(id, n) asm volatile("bar.sync " #id ", " #n ";" ::: "memory")
__device__ __forceinline__ void fence_async_smem() { asm volatile("fence.proxy.async.shared::cta;" ::: "memory"); }
__device__ __forceinline__ void fence_async_all() { asm volatile("fence.proxy.async;" ::: "memory"); }
__device__ __forceinline__ void tma2d(uint32_t dst, const CUtensorMap* tm, int c0, int c1, uint32_t bar) {
  asm volatile("cp.async.bulk.tensor.2d.shared::cluster.global.mbarrier::complete_tx::bytes [%0], [%1, {%3, %4}], [%2];"
               ::"r"(dst), "l"(tm), "r"(bar), "r"(c0), "r"(c1) : "memory");
}
__device__ __forceinline__ void tma3d(uint32_t dst, const CUtensorMap* tm, int c0, int c1, int c2, uint32_t bar) {
  asm volatile("cp.async.bulk.tensor.3d.shared::cluster.global.mbarrier::complete_tx::bytes [%0], [%1, {%3, %4, %5}], [%2];"
               ::"r"(dst), "l"(tm), "r"(bar), "r"(c0), "r"(c1), "r"(c2) : "memory");
}
__device__ __forceinline__ void tma2d_store(const CUtensorMap* tm, uint32_t src, int c0, int c1) {
  asm volatile("cp.async.bulk.tensor.2d.global.shared::cta.bulk_group [%0, {%2, %3}], [%1];" ::"l"(tm), "r"(src), "r"(c0), "r"(c1) : "memory");
}
__device__ __forceinline__ void bulk_load(uint32_t dst, const void* src, uint32_t bytes, uint32_t bar) {
  asm volatile("cp.async.bulk.shared::cluster.global.mbarrier::complete_tx::bytes [%0], [%1], %2, [%3];" ::"r"(dst), "l"(src), "r"(bytes), "r"(bar) : "memory");
}
__device__ __forceinline__ void bulk_store(void* dst, uint32_t src, uint32_t bytes) {
  asm volatile("cp.async.bulk.global.shared::cta.bulk_group [%0], [%1], %2;" ::"l"(dst), "r"(src), "r"(bytes) : "memory");
}
__device__ __forceinline__ void bulk_commit() { asm volatile("cp.async.bulk.commit_group;" ::: "memory"); }
template <int N> __device__ __forceinline__ void bulk_wait_read() { asm volatile("cp.async.bulk.wait_group.read %0;" ::"n"(N) : "memory"); }
template <int N> __device__ __forceinline__ void bulk_wait() { asm volatile("cp.async.bulk.wait_group %0;" ::"n"(N) : "memory"); }
__device__ __forceinline__ void red_release(unsigned* p) { asm volatile("red.release.gpu.global.add.u32 [%0], 1;" ::"l"(p) : "memory"); }
__device__ __forceinline__ void poll_acquire(const unsigned* p, unsigned target) {
  long long t0 = clock64();
  while (true) {
    unsigned v;
    asm volatile("ld.acquire.gpu.global.u32 %0, [%1];" : "=r"(v) : "l"(p) : "memory");
    if ((int)(v - target) >= 0) break;
    if (clock64() - t0 > SPIN_CLKS) __trap();
  }
}
__device__ __forceinline__ bool last_of_two(uint32_t a) {
  uint32_t o;
  asm volatile("atom.acq_rel.cta.shared::cta.add.u32 %0, [%1], 1;" : "=r"(o) : "r"(a) : "memory");
  return o == 1;
}
__device__ __forceinline__ void wg_fence() { asm volatile("wgmma.fence.sync.aligned;" ::: "memory"); }
__device__ __forceinline__ void wg_commit() { asm volatile("wgmma.commit_group.sync.aligned;" ::: "memory"); }
template <int N> __device__ __forceinline__ void wg_wait() { asm volatile("wgmma.wait_group.sync.aligned %0;" ::"n"(N) : "memory"); }
template <int N> __device__ __forceinline__ void reg_pin(float* d) {
#pragma unroll
  for (int i = 0; i < N; i++) asm volatile("" : "+f"(d[i])::"memory");
}
__device__ __forceinline__ uint64_t mkdesc(uint32_t addr, uint32_t lbo, uint32_t sbo, uint32_t swz) {
  return (uint64_t)((addr & 0x3FFFF) >> 4) | ((uint64_t)(lbo >> 4) << 16) | ((uint64_t)(sbo >> 4) << 32) | ((uint64_t)swz << 62);
}
__device__ __forceinline__ uint32_t lds32(uint32_t a) { uint32_t v; asm volatile("ld.shared.b32 %0, [%1];" : "=r"(v) : "r"(a)); return v; }
__device__ __forceinline__ float lds32f(uint32_t a) { float v; asm volatile("ld.shared.f32 %0, [%1];" : "=f"(v) : "r"(a)); return v; }
__device__ __forceinline__ uint2 lds64(uint32_t a) { uint2 v; asm volatile("ld.shared.v2.b32 {%0,%1}, [%2];" : "=r"(v.x), "=r"(v.y) : "r"(a)); return v; }
__device__ __forceinline__ uint4 lds128(uint32_t a) { uint4 v; asm volatile("ld.shared.v4.b32 {%0,%1,%2,%3}, [%4];" : "=r"(v.x), "=r"(v.y), "=r"(v.z), "=r"(v.w) : "r"(a)); return v; }
__device__ __forceinline__ float4 lds128f(uint32_t a) { float4 v; asm volatile("ld.shared.v4.f32 {%0,%1,%2,%3}, [%4];" : "=f"(v.x), "=f"(v.y), "=f"(v.z), "=f"(v.w) : "r"(a)); return v; }
__device__ __forceinline__ void sts16(uint32_t a, unsigned short v) { asm volatile("st.shared.b16 [%0], %1;" ::"r"(a), "h"(v) : "memory"); }
__device__ __forceinline__ void sts32(uint32_t a, uint32_t v) { asm volatile("st.shared.b32 [%0], %1;" ::"r"(a), "r"(v) : "memory"); }
__device__ __forceinline__ void sts32f(uint32_t a, float v) { asm volatile("st.shared.f32 [%0], %1;" ::"r"(a), "f"(v) : "memory"); }
__device__ __forceinline__ void sts64(uint32_t a, uint32_t x, uint32_t y) { asm volatile("st.shared.v2.b32 [%0], {%1,%2};" ::"r"(a), "r"(x), "r"(y) : "memory"); }
__device__ __forceinline__ void sts64f(uint32_t a, float x, float y) { asm volatile("st.shared.v2.f32 [%0], {%1,%2};" ::"r"(a), "f"(x), "f"(y) : "memory"); }
__device__ __forceinline__ void sts128(uint32_t a, uint32_t x, uint32_t y, uint32_t z, uint32_t w) { asm volatile("st.shared.v4.b32 [%0], {%1,%2,%3,%4};" ::"r"(a), "r"(x), "r"(y), "r"(z), "r"(w) : "memory"); }
__device__ __forceinline__ void sts128f(uint32_t a, float x, float y, float z, float w) { asm volatile("st.shared.v4.f32 [%0], {%1,%2,%3,%4};" ::"r"(a), "f"(x), "f"(y), "f"(z), "f"(w) : "memory"); }
__device__ __forceinline__ void stsm4(uint32_t a, uint32_t r0, uint32_t r1, uint32_t r2, uint32_t r3) {
  asm volatile("stmatrix.sync.aligned.m8n8.x4.shared.b16 [%0], {%1,%2,%3,%4};" ::"r"(a), "r"(r0), "r"(r1), "r"(r2), "r"(r3) : "memory");
}
__device__ __forceinline__ void stsm2(uint32_t a, uint32_t r0, uint32_t r1) {
  asm volatile("stmatrix.sync.aligned.m8n8.x2.shared.b16 [%0], {%1,%2};" ::"r"(a), "r"(r0), "r"(r1) : "memory");
}
__device__ __forceinline__ void stsm4t(uint32_t a, uint32_t r0, uint32_t r1, uint32_t r2, uint32_t r3) {
  asm volatile("stmatrix.sync.aligned.m8n8.x4.trans.shared.b16 [%0], {%1,%2,%3,%4};" ::"r"(a), "r"(r0), "r"(r1), "r"(r2), "r"(r3) : "memory");
}
__device__ __forceinline__ void ldsm4(uint32_t a, uint32_t& r0, uint32_t& r1, uint32_t& r2, uint32_t& r3) {
  asm volatile("ldmatrix.sync.aligned.m8n8.x4.shared.b16 {%0,%1,%2,%3}, [%4];" : "=r"(r0), "=r"(r1), "=r"(r2), "=r"(r3) : "r"(a) : "memory");
}
__device__ __forceinline__ void ldsm4t(uint32_t a, uint32_t& r0, uint32_t& r1, uint32_t& r2, uint32_t& r3) {
  asm volatile("ldmatrix.sync.aligned.m8n8.x4.trans.shared.b16 {%0,%1,%2,%3}, [%4];" : "=r"(r0), "=r"(r1), "=r"(r2), "=r"(r3) : "r"(a) : "memory");
}
__device__ __forceinline__ uint32_t pack_bf16(float lo, float hi) { uint32_t r; asm("cvt.rn.bf16x2.f32 %0, %1, %2;" : "=r"(r) : "f"(hi), "f"(lo)); return r; }
__device__ __forceinline__ uint32_t pack_f16(float lo, float hi) { uint32_t r; asm("cvt.rn.f16x2.f32 %0, %1, %2;" : "=r"(r) : "f"(hi), "f"(lo)); return r; }
__device__ __forceinline__ float bf_lo(uint32_t v) { return __uint_as_float(v << 16); }
__device__ __forceinline__ float bf_hi(uint32_t v) { return __uint_as_float(v & 0xffff0000u); }
__device__ __forceinline__ float bfr(float v) { return __bfloat162float(__float2bfloat16_rn(v)); }
__device__ __forceinline__ float tanh_fast(float x) { float y; asm("tanh.approx.f32 %0, %1;" : "=f"(y) : "f"(x)); return y; }
__device__ __forceinline__ float ex2(float x) { float y; asm("ex2.approx.ftz.f32 %0, %1;" : "=f"(y) : "f"(x)); return y; }
__device__ __forceinline__ uint32_t hadd2u(uint32_t a, uint32_t b) { uint32_t r; asm("add.rn.f16x2 %0, %1, %2;" : "=r"(r) : "r"(a), "r"(b)); return r; }
__device__ __forceinline__ uint32_t hsub2u(uint32_t a, uint32_t b) { uint32_t r; asm("sub.rn.f16x2 %0, %1, %2;" : "=r"(r) : "r"(a), "r"(b)); return r; }
__device__ __forceinline__ uint32_t hcmul(uint32_t z, uint32_t t, uint32_t tp) {
  __half2 zz = *reinterpret_cast<__half2*>(&z), tt = *reinterpret_cast<__half2*>(&t), pp = *reinterpret_cast<__half2*>(&tp);
  __half2 r = __hfma2(tt, __low2half2(zz), __hmul2(pp, __high2half2(zz)));
  return *reinterpret_cast<uint32_t*>(&r);
}
__device__ __forceinline__ float2 cexp_p(float lr, float wi, float p) {
  float m = ex2(lr * p), th = wi * p;
  return make_float2(m * __cosf(th), m * __sinf(th));
}
__device__ __forceinline__ float2 csq(float2 a) { return make_float2(fmaf(a.x, a.x, -a.y * a.y), 2.f * a.x * a.y); }
__device__ __forceinline__ float2 cmul(float2 a, float2 b) { return make_float2(fmaf(a.x, b.x, -a.y * b.y), fmaf(a.x, b.y, a.y * b.x)); }
__device__ __forceinline__ void mma_f16(float* c, uint32_t a0, uint32_t a1, uint32_t a2, uint32_t a3, uint32_t b0, uint32_t b1) {
  asm volatile("mma.sync.aligned.m16n8k16.row.col.f32.f16.f16.f32 {%0,%1,%2,%3}, {%4,%5,%6,%7}, {%8,%9}, {%0,%1,%2,%3};"
               : "+f"(c[0]), "+f"(c[1]), "+f"(c[2]), "+f"(c[3]) : "r"(a0), "r"(a1), "r"(a2), "r"(a3), "r"(b0), "r"(b1));
}
__device__ __forceinline__ void wgmma_ss_bf16_n216(float* d, uint64_t da, uint64_t db, int sd){
  asm volatile("{\n.reg .pred p;\nsetp.ne.b32 p, %110, 0;\nwgmma.mma_async.sync.aligned.m64n216k16.f32.bf16.bf16 {%0,%1,%2,%3,%4,%5,%6,%7,%8,%9,%10,%11,%12,%13,%14,%15,%16,%17,%18,%19,%20,%21,%22,%23,%24,%25,%26,%27,%28,%29,%30,%31,%32,%33,%34,%35,%36,%37,%38,%39,%40,%41,%42,%43,%44,%45,%46,%47,%48,%49,%50,%51,%52,%53,%54,%55,%56,%57,%58,%59,%60,%61,%62,%63,%64,%65,%66,%67,%68,%69,%70,%71,%72,%73,%74,%75,%76,%77,%78,%79,%80,%81,%82,%83,%84,%85,%86,%87,%88,%89,%90,%91,%92,%93,%94,%95,%96,%97,%98,%99,%100,%101,%102,%103,%104,%105,%106,%107}, %108, %109, p, 1, 1, 0, 1;\n}"
    : "+f"(d[0]),"+f"(d[1]),"+f"(d[2]),"+f"(d[3]),"+f"(d[4]),"+f"(d[5]),"+f"(d[6]),"+f"(d[7]),"+f"(d[8]),"+f"(d[9]),"+f"(d[10]),"+f"(d[11]),"+f"(d[12]),"+f"(d[13]),"+f"(d[14]),"+f"(d[15]),"+f"(d[16]),"+f"(d[17]),"+f"(d[18]),"+f"(d[19]),"+f"(d[20]),"+f"(d[21]),"+f"(d[22]),"+f"(d[23]),"+f"(d[24]),"+f"(d[25]),"+f"(d[26]),"+f"(d[27]),"+f"(d[28]),"+f"(d[29]),"+f"(d[30]),"+f"(d[31]),"+f"(d[32]),"+f"(d[33]),"+f"(d[34]),"+f"(d[35]),"+f"(d[36]),"+f"(d[37]),"+f"(d[38]),"+f"(d[39]),"+f"(d[40]),"+f"(d[41]),"+f"(d[42]),"+f"(d[43]),"+f"(d[44]),"+f"(d[45]),"+f"(d[46]),"+f"(d[47]),"+f"(d[48]),"+f"(d[49]),"+f"(d[50]),"+f"(d[51]),"+f"(d[52]),"+f"(d[53]),"+f"(d[54]),"+f"(d[55]),"+f"(d[56]),"+f"(d[57]),"+f"(d[58]),"+f"(d[59]),"+f"(d[60]),"+f"(d[61]),"+f"(d[62]),"+f"(d[63]),"+f"(d[64]),"+f"(d[65]),"+f"(d[66]),"+f"(d[67]),"+f"(d[68]),"+f"(d[69]),"+f"(d[70]),"+f"(d[71]),"+f"(d[72]),"+f"(d[73]),"+f"(d[74]),"+f"(d[75]),"+f"(d[76]),"+f"(d[77]),"+f"(d[78]),"+f"(d[79]),"+f"(d[80]),"+f"(d[81]),"+f"(d[82]),"+f"(d[83]),"+f"(d[84]),"+f"(d[85]),"+f"(d[86]),"+f"(d[87]),"+f"(d[88]),"+f"(d[89]),"+f"(d[90]),"+f"(d[91]),"+f"(d[92]),"+f"(d[93]),"+f"(d[94]),"+f"(d[95]),"+f"(d[96]),"+f"(d[97]),"+f"(d[98]),"+f"(d[99]),"+f"(d[100]),"+f"(d[101]),"+f"(d[102]),"+f"(d[103]),"+f"(d[104]),"+f"(d[105]),"+f"(d[106]),"+f"(d[107]) : "l"(da), "l"(db), "r"(sd));
}
__device__ __forceinline__ void wgmma_ss_bf16_n160(float* d, uint64_t da, uint64_t db, int sd){
  asm volatile("{\n.reg .pred p;\nsetp.ne.b32 p, %82, 0;\nwgmma.mma_async.sync.aligned.m64n160k16.f32.bf16.bf16 {%0,%1,%2,%3,%4,%5,%6,%7,%8,%9,%10,%11,%12,%13,%14,%15,%16,%17,%18,%19,%20,%21,%22,%23,%24,%25,%26,%27,%28,%29,%30,%31,%32,%33,%34,%35,%36,%37,%38,%39,%40,%41,%42,%43,%44,%45,%46,%47,%48,%49,%50,%51,%52,%53,%54,%55,%56,%57,%58,%59,%60,%61,%62,%63,%64,%65,%66,%67,%68,%69,%70,%71,%72,%73,%74,%75,%76,%77,%78,%79}, %80, %81, p, 1, 1, 0, 1;\n}"
    : "+f"(d[0]),"+f"(d[1]),"+f"(d[2]),"+f"(d[3]),"+f"(d[4]),"+f"(d[5]),"+f"(d[6]),"+f"(d[7]),"+f"(d[8]),"+f"(d[9]),"+f"(d[10]),"+f"(d[11]),"+f"(d[12]),"+f"(d[13]),"+f"(d[14]),"+f"(d[15]),"+f"(d[16]),"+f"(d[17]),"+f"(d[18]),"+f"(d[19]),"+f"(d[20]),"+f"(d[21]),"+f"(d[22]),"+f"(d[23]),"+f"(d[24]),"+f"(d[25]),"+f"(d[26]),"+f"(d[27]),"+f"(d[28]),"+f"(d[29]),"+f"(d[30]),"+f"(d[31]),"+f"(d[32]),"+f"(d[33]),"+f"(d[34]),"+f"(d[35]),"+f"(d[36]),"+f"(d[37]),"+f"(d[38]),"+f"(d[39]),"+f"(d[40]),"+f"(d[41]),"+f"(d[42]),"+f"(d[43]),"+f"(d[44]),"+f"(d[45]),"+f"(d[46]),"+f"(d[47]),"+f"(d[48]),"+f"(d[49]),"+f"(d[50]),"+f"(d[51]),"+f"(d[52]),"+f"(d[53]),"+f"(d[54]),"+f"(d[55]),"+f"(d[56]),"+f"(d[57]),"+f"(d[58]),"+f"(d[59]),"+f"(d[60]),"+f"(d[61]),"+f"(d[62]),"+f"(d[63]),"+f"(d[64]),"+f"(d[65]),"+f"(d[66]),"+f"(d[67]),"+f"(d[68]),"+f"(d[69]),"+f"(d[70]),"+f"(d[71]),"+f"(d[72]),"+f"(d[73]),"+f"(d[74]),"+f"(d[75]),"+f"(d[76]),"+f"(d[77]),"+f"(d[78]),"+f"(d[79]) : "l"(da), "l"(db), "r"(sd));
}
__device__ __forceinline__ void wgmma_rs_f16_n32(float* d, uint32_t a0, uint32_t a1, uint32_t a2, uint32_t a3, uint64_t db, int sd){
  asm volatile("{\n.reg .pred p;\nsetp.ne.b32 p, %21, 0;\nwgmma.mma_async.sync.aligned.m64n32k16.f32.f16.f16 {%0,%1,%2,%3,%4,%5,%6,%7,%8,%9,%10,%11,%12,%13,%14,%15}, {%16,%17,%18,%19}, %20, p, 1, 1, 0;\n}"
    : "+f"(d[0]),"+f"(d[1]),"+f"(d[2]),"+f"(d[3]),"+f"(d[4]),"+f"(d[5]),"+f"(d[6]),"+f"(d[7]),"+f"(d[8]),"+f"(d[9]),"+f"(d[10]),"+f"(d[11]),"+f"(d[12]),"+f"(d[13]),"+f"(d[14]),"+f"(d[15]) : "r"(a0), "r"(a1), "r"(a2), "r"(a3), "l"(db), "r"(sd));
}
__device__ __forceinline__ void wgmma_rs_f16_n24(float* d, uint32_t a0, uint32_t a1, uint32_t a2, uint32_t a3, uint64_t db, int sd){
  asm volatile("{\n.reg .pred p;\nsetp.ne.b32 p, %17, 0;\nwgmma.mma_async.sync.aligned.m64n24k16.f32.f16.f16 {%0,%1,%2,%3,%4,%5,%6,%7,%8,%9,%10,%11}, {%12,%13,%14,%15}, %16, p, 1, 1, 1;\n}"
    : "+f"(d[0]),"+f"(d[1]),"+f"(d[2]),"+f"(d[3]),"+f"(d[4]),"+f"(d[5]),"+f"(d[6]),"+f"(d[7]),"+f"(d[8]),"+f"(d[9]),"+f"(d[10]),"+f"(d[11]) : "r"(a0), "r"(a1), "r"(a2), "r"(a3), "l"(db), "r"(sd));
}
__device__ __forceinline__ void wgmma_rs_f16_n16(float* d, uint32_t a0, uint32_t a1, uint32_t a2, uint32_t a3, uint64_t db, int sd){
  asm volatile("{\n.reg .pred p;\nsetp.ne.b32 p, %13, 0;\nwgmma.mma_async.sync.aligned.m64n16k16.f32.f16.f16 {%0,%1,%2,%3,%4,%5,%6,%7}, {%8,%9,%10,%11}, %12, p, 1, 1, 1;\n}"
    : "+f"(d[0]),"+f"(d[1]),"+f"(d[2]),"+f"(d[3]),"+f"(d[4]),"+f"(d[5]),"+f"(d[6]),"+f"(d[7]) : "r"(a0), "r"(a1), "r"(a2), "r"(a3), "l"(db), "r"(sd));
}

struct Params {
  const __nv_bfloat16 *x, *logA, *aimag, *cre, *cim, *logdt, *dskip, *w1, *b1, *w2, *b2;
};

template <int MODE>
__device__ __forceinline__ void windows(uint32_t ub, int c, uint4 prv, uint4 cur) {
  uint32_t w[8] = {prv.x, prv.y, prv.z, prv.w, cur.x, cur.y, cur.z, cur.w}, o[7], pe[7], v3[4], v5[4];
#pragma unroll
  for (int i = 0; i < 7; i++) { o[i] = __byte_perm(w[i], w[i + 1], 0x5432); pe[i] = hadd2u(w[i], o[i]); }
#pragma unroll
  for (int i = 0; i < 4; i++) { v3[i] = hadd2u(o[i + 2], pe[i + 3]); v5[i] = hadd2u(hadd2u(pe[i], pe[i + 1]), w[i + 2]); }
  sts128(ub + U_V5 + c * 16, v5[0], v5[1], v5[2], v5[3]);
  sts128(ub + U_V3 + c * 16, v3[0], v3[1], v3[2], v3[3]);
  if (MODE == 2) {
    uint32_t w9[4], v7[4];
#pragma unroll
    for (int i = 0; i < 4; i++) { uint32_t s8 = hadd2u(v5[i], v3[i]); w9[i] = hadd2u(s8, w[i + 4]); v7[i] = hsub2u(s8, w[i]); }
    sts128(ub + U_P2 + c * 16, pe[3], pe[4], pe[5], pe[6]);
    sts128(ub + U_V7 + (c & 1) * U_HS + (c >> 1) * 16, v7[0], v7[1], v7[2], v7[3]);
    if (c < 127) sts128(ub + U_V9 + ((c + 1) & 1) * U_HS + ((c + 1) >> 1) * 16, w9[0], w9[1], w9[2], w9[3]);
  }
}

__global__ void __cluster_dims__(2, 1, 1) __launch_bounds__(384, 1)
fused_kernel(const __grid_constant__ CUtensorMap tm_x, const __grid_constant__ CUtensorMap tm_w1a,
             const __grid_constant__ CUtensorMap tm_w1b, const __grid_constant__ CUtensorMap tm_hst,
             const __grid_constant__ CUtensorMap tm_hld, const __grid_constant__ CUtensorMap tm_w2,
             const __grid_constant__ CUtensorMap tm_xe, const __grid_constant__ CUtensorMap tm_yc,
             const __grid_constant__ CUtensorMap tm_out, const Params P) {
  extern __shared__ __align__(1024) uint8_t smem_raw[];
  const uint32_t sb = smem_u32(smem_raw);
  const int tid = threadIdx.x, wg = __shfl_sync(~0u, tid >> 7, 0), warp = __shfl_sync(~0u, (tid >> 5) & 3, 0), lane = tid & 31, g = lane >> 2, q = lane & 3;
  const int bid = blockIdx.x, srank = bid & 1, cblk = (bid >> 1) & 3, iblk = bid >> 3, jblk = 4 * srank + cblk;
  auto bar = [&](int i) { return sb + BAR + 8 * i; };
  auto load1 = [&](int kc) {
    uint32_t fb = bar(B_FULL1 + kc % 3), dst = sb + (kc % 3) * S1_STAGE;
    mbar_expect(fb, S1_STAGE);
    tma2d(dst, &tm_x, kc * 64, iblk * 128, fb);
    tma3d(dst + S1_B, &tm_w1a, jblk * 216, kc * 64, 0, fb);
    tma2d(dst + S1_B + 6 * 4096, &tm_w1b, jblk * 216 + 192, kc * 64, fb);
  };
  auto load2a = [&](int m) {
    uint32_t fb = bar(B_FULLA + m % 3);
    mbar_expect(fb, S2_ASZ);
    tma2d(sb + S2_A + (m % 3) * S2_ASZ, &tm_hld, m == 13 ? 832 : srank * 896 + m * 64, iblk * 128, fb);
  };
  auto load2b = [&](int m) {
    uint32_t fb = bar(B_FULLB + (m & 3));
    mbar_expect(fb, S2_BSZ);
    tma3d(sb + S2_B + (m & 3) * S2_BSZ, &tm_w2, 0, m == 13 ? 832 : srank * 896 + m * 64, cblk * 5, fb);
  };
  if (tid == 0) {
    TLREC(0);
    if (sb & 1023) __trap();
    for (int i = 0; i < 11; i++) mbar_init(bar(i), 1);
    mbar_init(bar(B_EPI1), 128); mbar_init(bar(B_C8), 2);
    mbar_init(bar(B_PEER), 1); mbar_init(bar(B_XFULL), 1); mbar_init(bar(B_XCH), 1);
    asm volatile("fence.mbarrier_init.release.cluster;" ::: "memory");
    fence_async_smem();
    for (int kc = 0; kc < 3; kc++) load1(kc);
    mbar_expect(bar(B_XCH), 40960);
  }
  if (tid >= 32 && tid < 56) sts32(sb + REL + (tid - 32) * 4, 0);
  __syncthreads();
  asm volatile("barrier.cluster.arrive.release.aligned;" ::: "memory");

  if (wg == 2) {
    const int t = tid & 127;
    unsigned ep = 0;
    if (t == 0) {
      ep = g_epoch[bid] + 1;
      uint32_t pb = bar(B_PRM);
      mbar_expect(pb, 5120);
      bulk_load(sb + PRM, P.logA + bid * 640, 1280, pb);
      bulk_load(sb + PRM + 1280, P.aimag + bid * 640, 1280, pb);
      bulk_load(sb + PRM + 2560, P.cre + bid * 640, 1280, pb);
      bulk_load(sb + PRM + 3840, P.cim + bid * 640, 1280, pb);
    }
    __syncwarp();
    {
      const int tok0 = iblk * 128 + jblk * 16 + warp * 4;
      uint2 xr[4][5];
#pragma unroll
      for (int r = 0; r < 4; r++)
#pragma unroll
        for (int i = 0; i < 5; i++) xr[r][i] = __ldg(reinterpret_cast<const uint2*>(P.x + (tok0 + r) * D) + i * 32 + lane);
      uint4 wr[10];
      if (lane < 27) {
#pragma unroll
        for (int r = 0; r < 10; r++) wr[r] = __ldg(reinterpret_cast<const uint4*>(P.w1 + (iblk * 40 + warp * 10 + r) * F + jblk * 216) + lane);
      }
      for (int i = t; i < 5 * KA_SZ / 16; i += 128) sts128(sb + KA + i * 16, 0, 0, 0, 0);
      float mean[4], var[4];
#pragma unroll
      for (int r = 0; r < 4; r++) {
        float s = 0.f;
#pragma unroll
        for (int i = 0; i < 5; i++) s += (bf_lo(xr[r][i].x) + bf_hi(xr[r][i].x)) + (bf_lo(xr[r][i].y) + bf_hi(xr[r][i].y));
        mean[r] = s;
      }
#pragma unroll
      for (int o = 16; o; o >>= 1)
#pragma unroll
        for (int r = 0; r < 4; r++) mean[r] += __shfl_xor_sync(~0u, mean[r], o);
#pragma unroll
      for (int r = 0; r < 4; r++) {
        mean[r] *= (1.f / D);
        float s = 0.f;
#pragma unroll
        for (int i = 0; i < 5; i++) {
          float a = bf_lo(xr[r][i].x) - mean[r], b = bf_hi(xr[r][i].x) - mean[r], c = bf_lo(xr[r][i].y) - mean[r], d = bf_hi(xr[r][i].y) - mean[r];
          s += (a * a + b * b) + (c * c + d * d);
        }
        var[r] = s;
      }
#pragma unroll
      for (int o = 16; o; o >>= 1)
#pragma unroll
        for (int r = 0; r < 4; r++) var[r] += __shfl_xor_sync(~0u, var[r], o);
      float s1[4], s2[4], rs[4];
#pragma unroll
      for (int r = 0; r < 4; r++) {
        mean[r] = bfr(mean[r]);
        rs[r] = 1.f / bfr(sqrtf(bfr(bfr(var[r] * (1.f / D)) + 1e-5f)));
        int tk = warp * 4 + r;
        uint32_t rowa = sb + LNT + (((tk >> 1) & 1) * 8 + (tk >> 2) * 2 + (tk & 1)) * LNT_P + lane * 8;
        float a1 = 0.f, a2 = 0.f;
#pragma unroll
        for (int i = 0; i < 5; i++) {
          uint32_t d0 = pack_bf16(bf_lo(xr[r][i].x) - mean[r], bf_hi(xr[r][i].x) - mean[r]);
          uint32_t d1 = pack_bf16(bf_lo(xr[r][i].y) - mean[r], bf_hi(xr[r][i].y) - mean[r]);
          uint32_t n0 = pack_bf16(bf_lo(d0) * rs[r], bf_hi(d0) * rs[r]), n1 = pack_bf16(bf_lo(d1) * rs[r], bf_hi(d1) * rs[r]);
          float a = bf_lo(n0), b = bf_hi(n0), c = bf_lo(n1), d = bf_hi(n1);
          a1 += (a + b) + (c + d);
          a2 += (a * a + b * b) + (c * c + d * d);
          sts64(rowa + i * 256, pack_f16(a, b), pack_f16(c, d));
        }
        s1[r] = a1; s2[r] = a2;
      }
#pragma unroll
      for (int o = 16; o; o >>= 1)
#pragma unroll
        for (int r = 0; r < 4; r++) { s1[r] += __shfl_xor_sync(~0u, s1[r], o); s2[r] += __shfl_xor_sync(~0u, s2[r], o); }
#pragma unroll
      for (int r = 0; r < 4; r++) {
        float m2 = s1[r] * (1.f / D), v2 = fmaxf(s2[r] * (1.f / D) - m2 * m2, 0.f);
        float r2 = 1.f / bfr(sqrtf(bfr(bfr(v2) + 1e-5f)));
        if (lane == r) g_stats[tok0 + r] = make_float4(rs[r] * r2, -(mean[r] * rs[r] + bfr(m2)) * r2, mean[r], rs[r]);
      }
      if (lane < 27) {
        float cs[8] = {0, 0, 0, 0, 0, 0, 0, 0};
#pragma unroll
        for (int r = 0; r < 10; r++) {
          cs[0] += bf_lo(wr[r].x); cs[1] += bf_hi(wr[r].x); cs[2] += bf_lo(wr[r].y); cs[3] += bf_hi(wr[r].y);
          cs[4] += bf_lo(wr[r].z); cs[5] += bf_hi(wr[r].z); cs[6] += bf_lo(wr[r].w); cs[7] += bf_hi(wr[r].w);
        }
        sts128f(sb + CSS + warp * 864 + lane * 32, cs[0], cs[1], cs[2], cs[3]);
        sts128f(sb + CSS + warp * 864 + lane * 32 + 16, cs[4], cs[5], cs[6], cs[7]);
      }
      bar_sync(1, 128);
      {
        uint32_t la = sb + LNT + (lane & 15) * LNT_P + (lane >> 4) * 16 + warp * 320;
        __half* dst = g_xnT + (size_t)(warp * 160 + g) * L + iblk * 128 + jblk * 16 + q * 4;
#pragma unroll
        for (int i = 0; i < 10; i++) {
          uint32_t r0, r1, r2, r3;
          ldsm4t(la + i * 32, r0, r1, r2, r3);
          *reinterpret_cast<uint2*>(dst + (size_t)(i * 16) * L) = make_uint2(r0, r1);
          *reinterpret_cast<uint2*>(dst + (size_t)(i * 16 + 8) * L) = make_uint2(r2, r3);
        }
      }
      if (t < 54) {
        float4 a = lds128f(sb + CSS + t * 16), b = lds128f(sb + CSS + 864 + t * 16), c = lds128f(sb + CSS + 1728 + t * 16), d = lds128f(sb + CSS + 2592 + t * 16);
        *reinterpret_cast<float4*>(g_cs + iblk * F + jblk * 216 + t * 4) =
            make_float4((a.x + b.x) + (c.x + d.x), (a.y + b.y) + (c.y + d.y), (a.z + b.z) + (c.z + d.z), (a.w + b.w) + (c.w + d.w));
      }
      bar_sync(1, 128);
      if (t == 0) {
        red_release(&g_cnt[CNT_PREP * 32]);
        asm volatile("cp.async.bulk.prefetch.L2.global [%0], %1;" ::"l"(P.w2 + bid * 8640), "r"(17280) : "memory");
        TLREC(20);
      }
    }
    {
      mbar_wait(bar(B_PRM), 0);
      const __nv_bfloat16* prm = reinterpret_cast<const __nv_bfloat16*>(smem_raw + PRM);
#pragma unroll
      for (int ch = 0; ch < 5; ch++) {
        float cm = fmaxf(fabsf(__bfloat162float(prm[1280 + ch * 128 + t])), fabsf(__bfloat162float(prm[1920 + ch * 128 + t])));
        unsigned mx = __reduce_max_sync(~0u, __float_as_uint(cm));
        if (lane == 0) sts32(sb + SCL + 64 + ch * 16 + warp * 4, mx);
      }
      bar_sync(1, 128);
      const float fg = (float)g, fc4 = (float)(1032 + 128 * g);
#pragma unroll 1
      for (int ch = 0; ch < 5; ch++) {
        {
          uint4 m4 = lds128(sb + SCL + 64 + ch * 16);
          unsigned e = max(max(m4.x, m4.y), max(m4.z, m4.w)) >> 23;
          e = min(max(e, 1u), 252u);
          float sc = __uint_as_float((253u - e) << 23);
          float dt = bfr(expf(__bfloat162float(P.logdt[bid * 5 + ch])));
          if (t == 0) sts32f(sb + SCL + ch * 4, 2.f * dt * __uint_as_float((e + 1u) << 23));
          float lr = -bfr(expf(__bfloat162float(prm[ch * 128 + t]))) * dt * 1.4426950408889634f;
          float wi = __bfloat162float(prm[640 + ch * 128 + t]) * dt;
          float2 C = make_float2(__bfloat162float(prm[1280 + ch * 128 + t]) * sc, __bfloat162float(prm[1920 + ch * 128 + t]) * sc);
          float2 z64 = cexp_p(lr, wi, 64.f), z120 = cexp_p(lr, wi, 120.f), z258 = cexp_p(lr, wi, 258.f);
          float2 z128 = csq(z64), z256 = csq(z128), c64 = cmul(C, z64);
          float2 z378 = cmul(z258, z120), z516 = csq(z258), z636 = cmul(z516, z120), z756 = cmul(z636, z120), z876 = cmul(z756, z120);
          float f256 = fmaf(C.x, z256.x, -C.y * z256.y);
          __syncwarp();
          sts128(sb + TBA + t * 16, __float_as_uint(lr), __float_as_uint(wi), pack_f16(C.x, -C.y), pack_f16(-C.y, -C.x));
          sts128(sb + TBB + t * 16, pack_f16(c64.x, -c64.y), pack_f16(-c64.y, -c64.x), pack_f16(z128.x, z128.y), pack_f16(-z128.y, z128.x));
          sts128(sb + TB2 + t * 16, pack_f16(z258.x, z258.y), pack_f16(-z258.y, z258.x), pack_f16(z378.x, z378.y), pack_f16(-z378.y, z378.x));
          sts128(sb + TB3 + t * 32, pack_f16(z516.x, z516.y), pack_f16(-z516.y, z516.x), pack_f16(z636.x, z636.y), pack_f16(-z636.y, z636.x));
          sts128(sb + TB3 + t * 32 + 16, pack_f16(z756.x, z756.y), pack_f16(-z756.y, z756.x), pack_f16(z876.x, z876.y), pack_f16(-z876.y, z876.x));
#pragma unroll
          for (int o = 16; o; o >>= 1) f256 += __shfl_xor_sync(~0u, f256, o);
          if (lane == 0) sts32f(sb + PS + (ch & 1) * PS_SZ + warp * PS_W + 2560, f256);
          __syncwarp();
        }
        float acc[5][4];
#pragma unroll
        for (int i = 0; i < 5; i++) acc[i][0] = acc[i][1] = acc[i][2] = acc[i][3] = 0.f;
#pragma unroll
        for (int ks = 0; ks < 4; ks++) {
          uint32_t a[4], b[5][2];
#pragma unroll
          for (int hf = 0; hf < 2; hf++) {
            int n = warp * 32 + ks * 8 + hf * 4 + q;
            uint4 ta = lds128(sb + TBA + n * 16), tb = lds128(sb + TBB + n * 16);
            uint2 t2 = lds64(sb + TB2 + n * 16 + (g >> 2) * 8), t3 = lds64(sb + TB3 + n * 32 + (g >> 1) * 8);
            float lr = __uint_as_float(ta.x), wi = __uint_as_float(ta.y);
            float2 z1 = cexp_p(lr, wi, fg), zc = cexp_p(lr, wi, fc4);
            float2 z2 = csq(z1), z4 = csq(z2), z8 = csq(z4);
            uint32_t h1 = pack_f16(z1.x, z1.y), h2 = pack_f16(z2.x, z2.y), h4 = pack_f16(z4.x, z4.y), h8 = pack_f16(z8.x, z8.y);
            a[hf * 2] = hcmul(h8, ta.z, ta.w);
            a[hf * 2 + 1] = hcmul(h8, tb.x, tb.y);
            b[0][hf] = h1;
            b[1][hf] = hcmul(h1, tb.z, tb.w);
            b[2][hf] = hcmul(h2, t2.x, t2.y);
            b[3][hf] = hcmul(h4, t3.x, t3.y);
            b[4][hf] = pack_f16(zc.x, zc.y);
          }
#pragma unroll
          for (int i = 0; i < 5; i++) mma_f16(acc[i], a[0], a[1], a[2], a[3], b[i][0], b[i][1]);
        }
        uint32_t ps = sb + PS + (ch & 1) * PS_SZ;
#pragma unroll
        for (int i = 0; i < 5; i++) {
          sts64f(ps + warp * PS_W + i * 512 + lane * 8, acc[i][0], acc[i][1]);
          sts64f(ps + warp * PS_W + i * 512 + 256 + lane * 8, acc[i][2], acc[i][3]);
        }
        bar_sync(1, 128);
        {
          float v[5];
#pragma unroll
          for (int i = 0; i < 5; i++)
            v[i] = (lds32f(ps + i * 512 + t * 4) + lds32f(ps + PS_W + i * 512 + t * 4)) + (lds32f(ps + 2 * PS_W + i * 512 + t * 4) + lds32f(ps + 3 * PS_W + i * 512 + t * 4));
          const uint32_t k0 = sb + KA + ch * KA_SZ;
          auto put = [&](int y, float val) {
            unsigned short h = __half_as_ushort(__float2half_rn(val));
            sts16(k0 + y * 2, h); sts16(k0 + KA_C1 - 2 + y * 2, h);
          };
          const int a = t >> 3, c = t & 7;
          put(783 - t, v[0]);
          put(783 - 128 - t, v[1]);
          int p2 = 258 + 128 * (c >> 2) + 2 * (c & 3) + 8 * a;
          put(783 - p2, v[2]);
          if (c & 1) { put(783 - p2 - 1, v[2]); put(783 - p2 + 1, v[2]); }
          put(((c & 1) ? 784 : 912) + 192 - (65 + 16 * (c >> 1) + a), v[3]);
          put(((a & 1) ? 0 : 128) + 128 - (65 + 8 * c + (a >> 1)), v[4]);
          if (t == 127) { put(783 - 514, v[2]); sts32f(sb + SCL + 32 + ch * 4, v[3]); }
          if (t == 0) {
            float f = (lds32f(ps + 2560) + lds32f(ps + PS_W + 2560)) + (lds32f(ps + 2 * PS_W + 2560) + lds32f(ps + 3 * PS_W + 2560));
            put(783 - 256, f); put(783 - 257, f);
          }
        }
      }
    }
    if (t == 0) { TLREC(21); poll_acquire(&g_cnt[CNT_PREP * 32], ep * 128); TLREC(22); }
    bar_sync(1, 128);
    const uint4* usrc = reinterpret_cast<const uint4*>(g_xnT + (size_t)bid * 5 * L);
    uint4 c0, p0, c1, p1;
    c0 = __ldcg(usrc + t); c1 = __ldcg(usrc + t + 128); p1 = __ldcg(usrc + t + 127);
    p0 = t ? __ldcg(usrc + t - 1) : make_uint4(0, 0, 0, 0);
    {
      float4 st = __ldcg(&g_stats[iblk * 128 + t]);
      if (t < 108) {
        float2 s = make_float2(0.f, 0.f);
#pragma unroll
        for (int i = 0; i < 16; i++) { float2 v = __ldcg(reinterpret_cast<const float2*>(g_cs + i * F + jblk * 216) + t); s.x += v.x; s.y += v.y; }
        uint32_t bb = __ldg(reinterpret_cast<const uint32_t*>(P.b1 + jblk * 216) + t);
        sts128f(sb + CSB + t * 16, s.x, bf_lo(bb), s.y, bf_hi(bb));
      }
      if (t < 40) {
        int col0 = cblk * 160 + srank * 80;
        uint32_t bb = __ldg(reinterpret_cast<const uint32_t*>(P.b2 + col0) + t), dd = __ldg(reinterpret_cast<const uint32_t*>(P.dskip + col0) + t);
        sts128f(sb + EP2 + t * 16, bf_lo(bb), bf_lo(dd), bf_hi(bb), bf_hi(dd));
      }
      sts128f(sb + RST + t * 16, st.x, st.y, st.z, st.w);
      mbar_arrive(bar(B_EPI1));
      if (t < 72) { uint32_t a = sb + UB + (t & 7) * U_P + (t >> 3) * 16; sts128(a, 0, 0, 0, 0); sts128(a + UB_SZ, 0, 0, 0, 0); }
      if (t == 72) { sts128(sb + UB + U_V9, 0, 0, 0, 0); sts128(sb + UB + UB_SZ + U_V9, 0, 0, 0, 0); sts128(sb + Y4, 0, 0, 0, 0); sts128(sb + Y8, 0, 0, 0, 0); }
    }
    if (t == 0) TLREC(23);
#pragma unroll 1
    for (int ch = 0; ch < 5; ch++) {
      const uint32_t ub = sb + UB + (ch & 1) * UB_SZ;
      sts128(ub + (t & 7) * U_P + ((t >> 3) + 9) * 16, c0.x, c0.y, c0.z, c0.w);
      sts128(ub + (t & 7) * U_P + ((t >> 3) + 25) * 16, c1.x, c1.y, c1.z, c1.w);
      windows<2>(ub, t, p0, c0);
      if (warp < 2) windows<1>(ub, t + 128, p1, c1);
      fence_async_smem();
      if (ch < 4) {
        usrc += 256;
        c0 = __ldcg(usrc + t); c1 = __ldcg(usrc + t + 128); p1 = __ldcg(usrc + t + 127);
        p0 = t ? __ldcg(usrc + t - 1) : make_uint4(0, 0, 0, 0);
      }
      if (t == 0) bulk_wait_read<1>();
      bar_sync(1, 128);
      const uint32_t ka = sb + KA + ch * KA_SZ + ((g & 1) ? 0 : KA_C1) + 4 * (q + ((63 - g) >> 1) - 8 * warp);
      float aD[16], a4[12], a4b[8], a8[8];
      uint32_t R[9];
      auto loadR = [&](int n0) {
#pragma unroll
        for (int i = 0; i < 9; i++) R[i] = lds32(ka + 16 * (n0 - 1 + i));
      };
      const uint64_t d9 = mkdesc(ub + U_V9, 128, U_HS, 0), d7 = mkdesc(ub + U_V7, 128, U_HS, 0);
      const uint64_t d5 = mkdesc(ub + U_V5, 128, 1024, 0), d3 = mkdesc(ub + U_V3, 128, 1024, 0);
      const uint64_t du = mkdesc(ub + U_U, U_P, 128, 0);
      loadR(0); wg_fence();
#pragma unroll
      for (int m = 0; m < 4; m++) wgmma_rs_f16_n16(a8, R[2 * m + 1], R[2 * m], R[2 * m + 2], R[2 * m + 1], d9 + m * 16, m);
      wg_commit();
      loadR(16); wg_fence();
#pragma unroll
      for (int m = 0; m < 4; m++) wgmma_rs_f16_n16(a8, R[2 * m + 1], R[2 * m], R[2 * m + 2], R[2 * m + 1], d7 + m * 16, 1);
      wg_commit();
      loadR(98 + 8); wg_fence();
#pragma unroll
      for (int m = 0; m < 4; m++) wgmma_rs_f16_n24(a4, R[2 * m + 1], R[2 * m], R[2 * m + 2], R[2 * m + 1], d5 + m * 16, m);
      wg_commit(); wg_wait<2>();
      loadR(98); wg_fence();
#pragma unroll
      for (int m = 0; m < 4; m++) wgmma_rs_f16_n16(a4b, R[2 * m + 1], R[2 * m], R[2 * m + 2], R[2 * m + 1], d5 + m * 16, m);
      wg_commit(); wg_wait<2>();
      loadR(114 + 8); wg_fence();
#pragma unroll
      for (int m = 0; m < 4; m++) wgmma_rs_f16_n24(a4, R[2 * m + 1], R[2 * m], R[2 * m + 2], R[2 * m + 1], d3 + m * 16, 1);
      wg_commit(); wg_wait<2>();
      loadR(114); wg_fence();
#pragma unroll
      for (int m = 0; m < 4; m++) wgmma_rs_f16_n16(a4b, R[2 * m + 1], R[2 * m], R[2 * m + 2], R[2 * m + 1], d3 + m * 16, 1);
      wg_commit(); wg_wait<2>();
      {
        uint32_t r0 = lds32(ka + 16 * 23), r1 = lds32(ka + 16 * 24), r2 = lds32(ka + 16 * 25);
        wg_fence();
        wgmma_rs_f16_n32(aD, r1, r0, r2, r1, du + 6 * (U_P / 16), 0);
        wg_commit();
      }
#pragma unroll
      for (int blk = 0; blk < 9; blk++) {
        loadR(26 + 8 * blk); wg_fence();
#pragma unroll
        for (int m = 0; m < 4; m++) wgmma_rs_f16_n32(aD, R[2 * m + 1], R[2 * m], R[2 * m + 2], R[2 * m + 1], du + 2 * m * (U_P / 16) + blk + 1, 1);
        wg_commit(); wg_wait<2>();
        if (blk == 1) {
          reg_pin<12>(a4); reg_pin<8>(a4b); reg_pin<8>(a8);
          const float f1024 = lds32f(sb + SCL + 32 + ch * 4);
#pragma unroll
          for (int al = 0; al < 3; al++)
#pragma unroll
            for (int v = 0; v < 2; v++) {
              int x = 512 * al + 8 * (16 * warp + g + 8 * v) + 2 * q;
              float e0 = a4[al * 4 + v * 2], e1 = a4[al * 4 + v * 2 + 1];
              if (al > 0) {
                uint32_t pp = lds32(ub + U_P2 + (x - 512) * 2);
                float2 pf = __half22float2(*reinterpret_cast<__half2*>(&pp));
                e0 = fmaf(f1024, pf.x, e0 + a4b[al * 4 - 4 + v * 2]); e1 = fmaf(f1024, pf.y, e1 + a4b[al * 4 - 3 + v * 2]);
              }
              x += 2;
              sts64f(sb + Y4 + (x + 4 * (x >> 6)) * 4, e0, e1);
            }
#pragma unroll
          for (int h = 0; h < 2; h++)
#pragma unroll
            for (int v = 0; v < 2; v++) {
              int x = 16 * (16 * warp + g + 8 * v) + 8 * h + 2 * q + 4;
              sts64f(sb + Y8 + (x + 4 * (x >> 6)) * 4, a8[h * 4 + v * 2], a8[h * 4 + v * 2 + 1]);
            }
        }
      }
      bar_sync(1, 128);
      wg_wait<0>();
      reg_pin<16>(aD);
      {
        const float osc = lds32f(sb + SCL + ch * 4);
        uint32_t pk[8];
#pragma unroll
        for (int h = 0; h < 4; h++)
#pragma unroll
          for (int v = 0; v < 2; v++) {
            float e0 = aD[h * 4 + v * 2], e1 = aD[h * 4 + v * 2 + 1];
            uint32_t o = (68 * 2 * q + 16 * warp + g + 8 * v) * 4;
            if (h >= 1) { e0 += lds32f(sb + Y4 + o + (h - 1) * 8 * 272); e1 += lds32f(sb + Y4 + o + (h - 1) * 8 * 272 + 272); }
            if (h >= 2) { e0 += lds32f(sb + Y8 + o + (h - 2) * 8 * 272); e1 += lds32f(sb + Y8 + o + (h - 2) * 8 * 272 + 272); }
            pk[h * 2 + v] = pack_bf16(e0 * osc, e1 * osc);
          }
        uint32_t oa = sb + OST + (ch & 1) * 4096 + ((lane >> 4) * 8 + (lane & 7)) * 128 + (((2 * warp + ((lane >> 3) & 1)) ^ (lane & 7)) * 16);
        stsm4t(oa, pk[0], pk[1], pk[2], pk[3]);
        stsm4t(oa + 2048, pk[4], pk[5], pk[6], pk[7]);
        fence_async_smem();
        bar_sync(1, 128);
        if (t == 0) { bulk_store(g_ycT + (size_t)(bid * 5 + ch) * L, sb + OST + (ch & 1) * 4096, 4096); bulk_commit(); TLREC(24 + ch); }
      }
    }
    asm volatile("barrier.cluster.wait.acquire.aligned;" ::: "memory");
    if (t == 0) {
      bulk_wait<0>();
      red_release(&g_cnt[(CNT_CONV + (bid >> 4)) * 32]);
      mbar_arrive_cluster(mapa(bar(B_PEER), srank ^ 1));
      TLREC(30);
      uint32_t fb = bar(B_XFULL);
      int col0 = cblk * 160 + srank * 80;
      mbar_expect(fb, 40960);
      tma2d(sb + XT, &tm_xe, col0, iblk * 128, fb);
      tma2d(sb + XT + 10240, &tm_xe, col0, iblk * 128 + 64, fb);
      poll_acquire(&g_cnt[(CNT_CONV + cblk * 2 + srank) * 32], ep * 16);
      fence_async_all();
      TLREC(31);
      tma2d(sb + YC, &tm_yc, iblk * 128, col0, fb);
      tma2d(sb + YC + 10240, &tm_yc, iblk * 128 + 64, col0, fb);
    }
  } else {
    const int t = tid & 127;
    unsigned ep = 0;
    if (tid == 0) ep = g_epoch[bid] + 1;
    const int row0 = wg * 64 + warp * 16 + g;
    {
      float acc[108];
#pragma unroll 1
      for (int kc = 0; kc < 10; kc++) {
        int st = kc % 3;
        mbar_wait(bar(B_FULL1 + st), (kc / 3) & 1);
        if (kc == 0 && t == 0) TLREC(1 + wg * 8);
        uint64_t da = mkdesc(sb + st * S1_STAGE + wg * 8192, 16, 1024, 1), db = mkdesc(sb + st * S1_STAGE + S1_B, 4096, 512, 2);
        wg_fence();
#pragma unroll
        for (int k = 0; k < 4; k++) wgmma_ss_bf16_n216(acc, da + k * 2, db + k * 64, kc | k);
        wg_commit();
        if (kc) {
          wg_wait<1>();
          if (t == 0) {
            if (kc == 9) mbar_arrive(bar(B_C8));
            else if (kc < 8 && last_of_two(sb + REL + kc * 4)) load1(kc + 2);
          }
          __syncwarp();
        }
      }
      wg_wait<0>();
      reg_pin<108>(acc);
      if (t == 0) {
        TLREC(2 + wg * 8);
        if (last_of_two(sb + REL)) for (int m = 0; m < 4; m++) load2b(m);
      }
      __syncwarp();
      mbar_wait(bar(B_EPI1), 0);
      mbar_wait(bar(B_C8), 0);
      const float4 s0 = lds128f(sb + RST + row0 * 16), s1 = lds128f(sb + RST + (row0 + 8) * 16);
      const uint32_t ha = sb + HST + wg * HST_WG + (warp * 16 + (lane & 15)) * 432 + (lane >> 4) * 16;
      auto gelu = [](float v) {
        float hv = 0.5f * v;
        return fmaf(hv, tanh_fast(v * fmaf(v * v, 0.0356774081f, 0.7978845608f)), hv);
      };
      uint32_t pk[4];
#pragma unroll
      for (int n = 0; n < 27; n++) {
        float4 cb = lds128f(sb + CSB + n * 64 + q * 16);
        float v0 = fmaf(s0.x, acc[n * 4], fmaf(s0.y, cb.x, cb.y)), v1 = fmaf(s0.x, acc[n * 4 + 1], fmaf(s0.y, cb.z, cb.w));
        float v2 = fmaf(s1.x, acc[n * 4 + 2], fmaf(s1.y, cb.x, cb.y)), v3 = fmaf(s1.x, acc[n * 4 + 3], fmaf(s1.y, cb.z, cb.w));
        pk[(n & 1) * 2] = pack_bf16(gelu(v0), gelu(v1));
        pk[(n & 1) * 2 + 1] = pack_bf16(gelu(v2), gelu(v3));
        if (n & 1) stsm4(ha + (n - 1) * 16, pk[0], pk[1], pk[2], pk[3]);
      }
      stsm2(ha - (lane >> 4) * 16 + 26 * 16, pk[0], pk[1]);
      fence_async_smem();
      if (wg) bar_sync(3, 128); else bar_sync(2, 128);
      if (t == 0) {
        TLREC(3 + wg * 8);
        tma2d_store(&tm_hst, sb + HST + wg * HST_WG, jblk * 216, iblk * 128 + wg * 64);
        bulk_commit();
        bulk_wait<0>();
        red_release(&g_cnt[(CNT_H + iblk * 2 + srank) * 32]);
        TLREC(4 + wg * 8);
        if (wg == 0) {
          poll_acquire(&g_cnt[(CNT_H + iblk * 2 + srank) * 32], ep * 8);
          fence_async_all();
          TLREC(18);
          for (int m = 0; m < 3; m++) load2a(m);
        }
      }
      __syncwarp();
    }
    asm volatile("barrier.cluster.wait.acquire.aligned;" ::: "memory");
    float acc[80];
#pragma unroll 1
    for (int m = 0; m < 13; m++) {
      int sa = m % 3, sl = m & 3;
      mbar_wait(bar(B_FULLB + sl), (m >> 2) & 1);
      mbar_wait(bar(B_FULLA + sa), (m / 3) & 1);
      if (m == 0 && t == 0) TLREC(5 + wg * 8);
      uint64_t da = mkdesc(sb + S2_A + sa * S2_ASZ + wg * 8192, 16, 1024, 1), db = mkdesc(sb + S2_B + sl * S2_BSZ, 4096, 512, 2);
      wg_fence();
#pragma unroll
      for (int k = 0; k < 4; k++) wgmma_ss_bf16_n160(acc, da + k * 2, db + k * 64, m | k);
      wg_commit();
      if (m) {
        wg_wait<1>();
        if (t == 0 && m < 12 && last_of_two(sb + REL + (9 + m) * 4)) {
          if (wg) fence_async_all();
          load2a(m + 2);
          if (m < 11) load2b(m + 3);
        }
        __syncwarp();
      }
    }
    {
      mbar_wait(bar(B_FULLB + 1), 1);
      mbar_wait(bar(B_FULLA + 1), 0);
      uint64_t da = mkdesc(sb + S2_A + S2_ASZ + wg * 8192, 16, 1024, 1) + srank * 4, db = mkdesc(sb + S2_B + S2_BSZ, 4096, 512, 2) + srank * 128;
      wg_fence();
      wgmma_ss_bf16_n160(acc, da, db, 1);
      wgmma_ss_bf16_n160(acc, da + 2, db + 64, 1);
      wg_commit();
    }
    wg_wait<0>();
    reg_pin<80>(acc);
    if (t == 0) TLREC(6 + wg * 8);
    mbar_wait_cl(bar(B_PEER), 0);
    {
      const uint32_t ra = mapa(sb + XCH + tid * 16, srank ^ 1), rb = mapa(bar(B_XCH), srank ^ 1);
#pragma unroll
      for (int n = 0; n < 10; n++) {
        float e0 = srank ? acc[n * 4] : acc[40 + n * 4], e1 = srank ? acc[n * 4 + 1] : acc[41 + n * 4];
        float e2 = srank ? acc[n * 4 + 2] : acc[42 + n * 4], e3 = srank ? acc[n * 4 + 3] : acc[43 + n * 4];
        asm volatile("st.async.weak.shared::cluster.mbarrier::complete_tx::bytes.v4.f32 [%0], {%1,%2,%3,%4}, [%5];"
                     ::"r"(ra + n * 4096), "f"(e0), "f"(e1), "f"(e2), "f"(e3), "r"(rb) : "memory");
      }
    }
    mbar_wait(bar(B_XFULL), 0);
    const float4 s0 = lds128f(sb + RST + row0 * 16), s1 = lds128f(sb + RST + (row0 + 8) * 16);
    const uint32_t xa = sb + XT + wg * 10240 + (warp * 16 + (lane & 15)) * 160 + (lane >> 4) * 16;
    const uint32_t ya = sb + YC + wg * 10240 + ((lane >> 4) * 8 + (lane & 7)) * 128 +
                        ((((2 * warp + ((lane >> 3) & 1)) ^ ((2 * iblk + wg) & 7)) ^ (lane & 7)) * 16);
    mbar_wait_cl(bar(B_XCH), 0);
    if (t == 0) TLREC(7 + wg * 8);
#pragma unroll
    for (int n2 = 0; n2 < 5; n2++) {
      uint32_t xv[4], yv[4], pk[4];
      ldsm4(xa + n2 * 32, xv[0], xv[1], xv[2], xv[3]);
      ldsm4t(ya + n2 * 2048, yv[0], yv[1], yv[2], yv[3]);
#pragma unroll
      for (int u = 0; u < 2; u++) {
        int n = n2 * 2 + u;
        float4 rv = lds128f(sb + XCH + n * 4096 + tid * 16), cb = lds128f(sb + EP2 + n * 64 + q * 16);
        float o[4] = {(srank ? acc[40 + n * 4] : acc[n * 4]) + rv.x + cb.x, (srank ? acc[41 + n * 4] : acc[n * 4 + 1]) + rv.y + cb.z,
                      (srank ? acc[42 + n * 4] : acc[n * 4 + 2]) + rv.z + cb.x, (srank ? acc[43 + n * 4] : acc[n * 4 + 3]) + rv.w + cb.z};
#pragma unroll
        for (int v = 0; v < 2; v++) {
          const float mu = v ? s1.z : s0.z, rs = v ? s1.w : s0.w;
          float x0 = bf_lo(xv[u * 2 + v]), x1 = bf_hi(xv[u * 2 + v]);
          uint32_t dd = pack_bf16(x0 - mu, x1 - mu);
          uint32_t nn = pack_bf16(bf_lo(dd) * rs, bf_hi(dd) * rs);
          float sa = fmaf(bf_lo(nn), cb.y, bf_lo(yv[u * 2 + v])), sc = fmaf(bf_hi(nn), cb.w, bf_hi(yv[u * 2 + v]));
          float h0 = 0.5f * o[v * 2], h1 = 0.5f * o[v * 2 + 1];
          float g0 = fmaf(h0, tanh_fast(h0), h0), g1 = fmaf(h1, tanh_fast(h1), h1);
          pk[u * 2 + v] = pack_bf16(fmaf(sa, g0, x0), fmaf(sc, g1, x1));
        }
      }
      stsm4(xa + n2 * 32, pk[0], pk[1], pk[2], pk[3]);
    }
    fence_async_smem();
    if (wg) bar_sync(3, 128); else bar_sync(2, 128);
    if (t == 0) {
      tma2d_store(&tm_out, sb + XT + wg * 10240, cblk * 160 + srank * 80, iblk * 128 + wg * 64);
      bulk_commit();
      if (wg == 0) g_epoch[bid] = ep;
      bulk_wait_read<0>();
      TLREC(8 + wg * 8);
    }
  }
}

typedef CUresult (*EncodeFn)(CUtensorMap*, CUtensorMapDataType, cuuint32_t, void*, const cuuint64_t*, const cuuint64_t*,
                             const cuuint32_t*, const cuuint32_t*, CUtensorMapInterleave, CUtensorMapSwizzle,
                             CUtensorMapL2promotion, CUtensorMapFloatOOBfill);

void make_map(EncodeFn fn, CUtensorMap* tm, const void* base, int rank, cuuint64_t d0, cuuint64_t d1, cuuint64_t d2,
              cuuint64_t s1, cuuint64_t s2, cuuint32_t b0, cuuint32_t b1, cuuint32_t b2, CUtensorMapSwizzle sw) {
  cuuint64_t dims[3] = {d0, d1, d2}, strides[2] = {s1, s2};
  cuuint32_t box[3] = {b0, b1, b2}, es[3] = {1, 1, 1};
  fn(tm, CU_TENSOR_MAP_DATA_TYPE_BFLOAT16, rank, const_cast<void*>(base), dims, strides, box, es, CU_TENSOR_MAP_INTERLEAVE_NONE,
     sw, CU_TENSOR_MAP_L2_PROMOTION_L2_128B, CU_TENSOR_MAP_FLOAT_OOB_FILL_NONE);
}

}

extern "C" void kernel_launch(void* const* d_in, const int* in_sizes, int n_in, void* d_out, int out_size) {
  static EncodeFn fn = nullptr;
  static void *hp = nullptr, *yp = nullptr;
  if (!fn) {
    void* p = nullptr;
    cudaDriverEntryPointQueryResult qr;
    cudaGetDriverEntryPoint("cuTensorMapEncodeTiled", &p, cudaEnableDefault, &qr);
    fn = (EncodeFn)p;
    cudaFuncSetAttribute(fused_kernel, cudaFuncAttributeMaxDynamicSharedMemorySize, SMEM_TOTAL);
    cudaGetSymbolAddress(&hp, g_h);
    cudaGetSymbolAddress(&yp, g_ycT);
  }
  typedef const __nv_bfloat16* bp;
  Params P{(bp)d_in[0], (bp)d_in[1], (bp)d_in[2], (bp)d_in[3], (bp)d_in[4], (bp)d_in[5], (bp)d_in[6],
           (bp)d_in[8], (bp)d_in[9], (bp)d_in[10], (bp)d_in[11]};
  CUtensorMap tx, tw1a, tw1b, thst, thld, tw2, txe, tyc, tout;
  make_map(fn, &tx, P.x, 2, D, L, 1, D * 2, 0, 64, 128, 1, CU_TENSOR_MAP_SWIZZLE_128B);
  make_map(fn, &tw1a, P.w1, 3, F, D, 6, F * 2, 64, 32, 64, 6, CU_TENSOR_MAP_SWIZZLE_64B);
  make_map(fn, &tw1b, P.w1, 2, F, D, 1, F * 2, 0, 32, 64, 1, CU_TENSOR_MAP_SWIZZLE_64B);
  make_map(fn, &thst, hp, 2, F, L, 1, F * 2, 0, 216, 64, 1, CU_TENSOR_MAP_SWIZZLE_NONE);
  make_map(fn, &thld, hp, 2, F, L, 1, F * 2, 0, 64, 128, 1, CU_TENSOR_MAP_SWIZZLE_128B);
  make_map(fn, &tw2, P.w2, 3, 32, F, 20, D * 2, 64, 32, 64, 5, CU_TENSOR_MAP_SWIZZLE_64B);
  make_map(fn, &txe, P.x, 2, D, L, 1, D * 2, 0, 80, 64, 1, CU_TENSOR_MAP_SWIZZLE_NONE);
  make_map(fn, &tyc, yp, 2, L, D, 1, L * 2, 0, 64, 80, 1, CU_TENSOR_MAP_SWIZZLE_128B);
  make_map(fn, &tout, d_out, 2, D, L, 1, D * 2, 0, 80, 64, 1, CU_TENSOR_MAP_SWIZZLE_NONE);
  fused_kernel<<<128, 384, SMEM_TOTAL, cudaStreamPerThread>>>(tx, tw1a, tw1b, thst, thld, tw2, txe, tyc, tout, P);
}
```

```cpp
#include <cuda_runtime.h>
#include <cuda_bf16.h>
#include <cuda_fp16.h>
#include <cuda.h>
#include <stdint.h>

namespace {

constexpr int L = 2048, D = 640, F = 1728;

__device__ __align__(1024) __half        g_xnT[D * L];
__device__ __align__(1024) __nv_bfloat16 g_h[L * F];
__device__ __align__(1024) __nv_bfloat16 g_yc[D * L];
__device__ __align__(128) float2 g_stats[L];
__device__ __align__(128) float g_cs[16 * F];
__device__ unsigned       g_cnt[200 * 32];
__device__ unsigned       g_epoch[128];
#define TLREC(slot) do {} while (0)
#define TLGT(slot) do {} while (0)
constexpr int CNT_PREP = 0, CNT_CONV = 1  , CNT_H = 8  ;

constexpr int S1_STAGE = 49152, S1_B = 16384;
constexpr int S2_A = 49152, S2_BSZ = 24576;
constexpr int S2_B0 = 114688;
constexpr int AUX = 147456;
constexpr int KA = AUX, KA_C1 = 1984, KA_SZ = 2 * KA_C1, KA_4 = 1120, KA_8 = KA_4 + 448;
constexpr int R0 = KA + 5 * KA_SZ, R_SZ = 59648;
constexpr int UU = R0, U_H = 2240;
constexpr int V5 = UU + 10 * U_H, V3 = V5 + 3328, V9 = V3 + 3328, V7 = V9 + 2176;
constexpr int PD = V7 + 2048, PD_H = 2368, P4 = PD + 4 * PD_H, P8 = P4 + 8960, P8_H = 1600;
constexpr int TBG = 2 * S1_STAGE, TB_SZ = 7168, TB2 = R0, PS = R0 + 4 * TB_SZ, PS_SZ = 2576;
constexpr int LNT = R0;
constexpr int YC = AUX, XCH = S2_BSZ, HALF = S2_B0 + S2_BSZ;
constexpr int MISC = R0 + R_SZ;
constexpr int CSB = MISC, RST = CSB + 1792, EP2 = RST + 1024, CSS = MISC, SCL = EP2 + 640, LS1 = SCL + 128, LS2 = SCL + 256, BAR = SCL + 512;
constexpr int SMEM_TOTAL = BAR + 512;
static_assert(P8 + 4 * P8_H <= MISC && PS + 12 * PS_SZ <= MISC && HALF + 8192 <= AUX && TBG + 8 * TB_SZ <= R0, "overflow");
static_assert(R0 % 128 == 0 && MISC % 128 == 0 && SMEM_TOTAL <= 232448, "smem");
enum { B_FULL1 = 0, B_FULLA = 3  , B_FULLB = 11, B_PEER = 14, B_YC = 15, B_XCH = 16, B_EPI1 = 17, B_C8 = 18 };
constexpr int REL = BAR + 256;

__device__ __forceinline__ uint32_t smem_u32(const void* p) { return (uint32_t)__cvta_generic_to_shared(p); }
__device__ __forceinline__ void mbar_init(uint32_t b, int c) { asm volatile("mbarrier.init.shared::cta.b64 [%0], %1;" ::"r"(b), "r"(c)); }
__device__ __forceinline__ void mbar_expect(uint32_t b, uint32_t bytes) { asm volatile("mbarrier.arrive.expect_tx.shared::cta.b64 _, [%0], %1;" ::"r"(b), "r"(bytes) : "memory"); }
__device__ __forceinline__ void mbar_arrive(uint32_t b) { asm volatile("mbarrier.arrive.shared::cta.b64 _, [%0];" ::"r"(b) : "memory"); }
__device__ __forceinline__ uint32_t mapa(uint32_t a, uint32_t cta) { uint32_t r; asm volatile("mapa.shared::cluster.u32 %0, %1, %2;" : "=r"(r) : "r"(a), "r"(cta)); return r; }
__device__ __forceinline__ void mbar_arrive_cluster(uint32_t ra) { asm volatile("mbarrier.arrive.shared::cluster.b64 _, [%0];" ::"r"(ra) : "memory"); }
#define MBAR_WAIT(SEM) \
  asm volatile("{\n.reg .pred p;\n.reg .u32 c;\nmov.u32 c, 0;\nW_LOOP:\nmbarrier.try_wait.parity" SEM ".shared::cta.b64 p, [%0], %1;\n@p bra.uni W_DONE;\n" \
               "add.u32 c, c, 1;\nsetp.lt.u32 p, c, 0x40000;\n@p bra.uni W_LOOP;\ntrap;\nW_DONE:\n}" ::"r"(b), "r"(ph) : "memory")
__device__ __forceinline__ void mbar_wait(uint32_t b, uint32_t ph) { MBAR_WAIT(""); }
__device__ __forceinline__ void mbar_wait_cl(uint32_t b, uint32_t ph) { MBAR_WAIT(".acquire.cluster"); }
#define bar_sync(id, n) asm volatile("bar.sync " #id ", " #n ";" ::: "memory")
__device__ __forceinline__ void fence_async_smem() { asm volatile("fence.proxy.async.shared::cta;" ::: "memory"); }
__device__ __forceinline__ void fence_async_all() { asm volatile("fence.proxy.async.global;" ::: "memory"); }
__device__ __forceinline__ void tma2d(uint32_t dst, const CUtensorMap* tm, int c0, int c1, uint32_t bar) {
  asm volatile("cp.async.bulk.tensor.2d.shared::cluster.global.mbarrier::complete_tx::bytes [%0], [%1, {%3, %4}], [%2];"
               ::"r"(dst), "l"(tm), "r"(bar), "r"(c0), "r"(c1) : "memory");
}
__device__ __forceinline__ bool elect() {
  uint32_t p;
  asm volatile("{\n.reg .pred p;\nelect.sync _|p, 0xffffffff;\nselp.u32 %0,1,0,p;\n}" : "=r"(p));
  return p;
}
__device__ __forceinline__ void bulk_load(uint32_t dst, const void* src, uint32_t bytes, uint32_t bar) {
  asm volatile("cp.async.bulk.shared::cluster.global.mbarrier::complete_tx::bytes [%0], [%1], %2, [%3];" ::"r"(dst), "l"(src), "r"(bytes), "r"(bar) : "memory");
}
__device__ __forceinline__ void bulk_store(void* dst, uint32_t src, uint32_t bytes) {
  asm volatile("cp.async.bulk.global.shared::cta.bulk_group [%0], [%1], %2;" ::"l"(dst), "r"(src), "r"(bytes) : "memory");
}
__device__ __forceinline__ void bulk_commit() { asm volatile("cp.async.bulk.commit_group;" ::: "memory"); }
template <int N> __device__ __forceinline__ void bulk_wait() { asm volatile("cp.async.bulk.wait_group %0;" ::"n"(N) : "memory"); }
__device__ __forceinline__ void red_release(unsigned* p) { asm volatile("red.release.gpu.global.add.u32 [%0], 1;" ::"l"(p) : "memory"); }
__device__ __forceinline__ void red_relaxed(unsigned* p) { asm volatile("red.relaxed.gpu.global.add.u32 [%0], 1;" ::"l"(p) : "memory"); }
__device__ __forceinline__ uint32_t ldg32(const void* p) { uint32_t v; asm volatile("ld.relaxed.gpu.global.b32 %0, [%1];" : "=r"(v) : "l"(p)); return v; }
__device__ __forceinline__ uint32_t ldg16(const void* p) { unsigned short v; asm volatile("ld.relaxed.gpu.global.b16 %0, [%1];" : "=h"(v) : "l"(p)); return v; }
__device__ __forceinline__ uint4 ldg128(const void* p) { uint4 v; asm volatile("ld.relaxed.gpu.global.v4.b32 {%0,%1,%2,%3}, [%4];" : "=r"(v.x), "=r"(v.y), "=r"(v.z), "=r"(v.w) : "l"(p)); return v; }
__device__ __forceinline__ float rstd(float var) {
  float s, r;
  asm("sqrt.approx.f32 %0, %1;" : "=f"(s) : "f"(__bfloat162float(__float2bfloat16_rn(__bfloat162float(__float2bfloat16_rn(var)) + 1e-5f))));
  asm("rcp.approx.f32 %0, %1;" : "=f"(r) : "f"(__bfloat162float(__float2bfloat16_rn(s))));
  return r;
}
__device__ __forceinline__ void poll_acquire(const unsigned* p, unsigned target) {
  asm volatile("{\n.reg .pred p;\n.reg .u32 c;\n.reg .s32 v;\nmov.u32 c, 0;\nP_LOOP:\nld.acquire.gpu.global.s32 v, [%0];\nsub.s32 v, v, %1;\nsetp.ge.s32 p, v, 0;\n@p bra P_DONE;\n"
               "add.u32 c, c, 1;\nsetp.lt.u32 p, c, 0x40000;\n@p bra P_LOOP;\ntrap;\nP_DONE:\n}" ::"l"(p), "r"(target) : "memory");
}
__device__ __forceinline__ bool last_of_two(uint32_t a) {
  uint32_t o;
  asm volatile("atom.relaxed.cta.shared::cta.add.u32 %0, [%1], 1;" : "=r"(o) : "r"(a) : "memory");
  return o == 1;
}
__device__ __forceinline__ void wg_fence() { asm volatile("wgmma.fence.sync.aligned;" ::: "memory"); }
__device__ __forceinline__ void wg_commit() { asm volatile("wgmma.commit_group.sync.aligned;" ::: "memory"); }
template <int N> __device__ __forceinline__ void wg_wait() { asm volatile("wgmma.wait_group.sync.aligned %0;" ::"n"(N) : "memory"); }
template <int N> __device__ __forceinline__ void reg_pin(float* d) {
#pragma unroll
  for (int i = 0; i < N; i++) asm volatile("" : "+f"(d[i])::"memory");
}
__device__ __forceinline__ uint64_t mkdesc(uint32_t addr, uint32_t lbo, uint32_t sbo, uint32_t swz) {
  return (uint64_t)((addr & 0x3FFFF) >> 4) | ((uint64_t)(lbo >> 4) << 16) | ((uint64_t)(sbo >> 4) << 32) | ((uint64_t)swz << 62);
}
__device__ __forceinline__ uint32_t lds32(uint32_t a) { uint32_t v; asm volatile("ld.shared.b32 %0, [%1];" : "=r"(v) : "r"(a)); return v; }
__device__ __forceinline__ float lds32f(uint32_t a) { float v; asm volatile("ld.shared.f32 %0, [%1];" : "=f"(v) : "r"(a)); return v; }
__device__ __forceinline__ uint2 lds64(uint32_t a) { uint2 v; asm volatile("ld.shared.v2.b32 {%0,%1}, [%2];" : "=r"(v.x), "=r"(v.y) : "r"(a)); return v; }
__device__ __forceinline__ uint4 lds128(uint32_t a) { uint4 v; asm volatile("ld.shared.v4.b32 {%0,%1,%2,%3}, [%4];" : "=r"(v.x), "=r"(v.y), "=r"(v.z), "=r"(v.w) : "r"(a)); return v; }
__device__ __forceinline__ float4 lds128f(uint32_t a) { float4 v; asm volatile("ld.shared.v4.f32 {%0,%1,%2,%3}, [%4];" : "=f"(v.x), "=f"(v.y), "=f"(v.z), "=f"(v.w) : "r"(a)); return v; }
__device__ __forceinline__ void sts16(uint32_t a, unsigned short v) { asm volatile("st.shared.b16 [%0], %1;" ::"r"(a), "h"(v) : "memory"); }
__device__ __forceinline__ void sts32(uint32_t a, uint32_t v) { asm volatile("st.shared.b32 [%0], %1;" ::"r"(a), "r"(v) : "memory"); }
__device__ __forceinline__ void sts32f(uint32_t a, float v) { asm volatile("st.shared.f32 [%0], %1;" ::"r"(a), "f"(v) : "memory"); }
__device__ __forceinline__ void sts64(uint32_t a, uint32_t x, uint32_t y) { asm volatile("st.shared.v2.b32 [%0], {%1,%2};" ::"r"(a), "r"(x), "r"(y) : "memory"); }
__device__ __forceinline__ void sts64f(uint32_t a, float x, float y) { asm volatile("st.shared.v2.f32 [%0], {%1,%2};" ::"r"(a), "f"(x), "f"(y) : "memory"); }
__device__ __forceinline__ void sts128(uint32_t a, uint32_t x, uint32_t y, uint32_t z, uint32_t w) { asm volatile("st.shared.v4.b32 [%0], {%1,%2,%3,%4};" ::"r"(a), "r"(x), "r"(y), "r"(z), "r"(w) : "memory"); }
__device__ __forceinline__ void sts128f(uint32_t a, float x, float y, float z, float w) { asm volatile("st.shared.v4.f32 [%0], {%1,%2,%3,%4};" ::"r"(a), "f"(x), "f"(y), "f"(z), "f"(w) : "memory"); }
__device__ __forceinline__ void stsm4(uint32_t a, uint32_t r0, uint32_t r1, uint32_t r2, uint32_t r3) {
  asm volatile("stmatrix.sync.aligned.m8n8.x4.shared.b16 [%0], {%1,%2,%3,%4};" ::"r"(a), "r"(r0), "r"(r1), "r"(r2), "r"(r3) : "memory");
}
__device__ __forceinline__ void stsm4t(uint32_t a, uint32_t r0, uint32_t r1, uint32_t r2, uint32_t r3) {
  asm volatile("stmatrix.sync.aligned.m8n8.x4.trans.shared.b16 [%0], {%1,%2,%3,%4};" ::"r"(a), "r"(r0), "r"(r1), "r"(r2), "r"(r3) : "memory");
}
__device__ __forceinline__ void ldsm4t(uint32_t a, uint32_t& r0, uint32_t& r1, uint32_t& r2, uint32_t& r3) {
  asm volatile("ldmatrix.sync.aligned.m8n8.x4.trans.shared.b16 {%0,%1,%2,%3}, [%4];" : "=r"(r0), "=r"(r1), "=r"(r2), "=r"(r3) : "r"(a) : "memory");
}
__device__ __forceinline__ uint32_t pack_bf16(float lo, float hi) { uint32_t r; asm("cvt.rn.bf16x2.f32 %0, %1, %2;" : "=r"(r) : "f"(hi), "f"(lo)); return r; }
__device__ __forceinline__ uint32_t pack_f16(float lo, float hi) { uint32_t r; asm("cvt.rn.f16x2.f32 %0, %1, %2;" : "=r"(r) : "f"(hi), "f"(lo)); return r; }
__device__ __forceinline__ float bf_lo(uint32_t v) { return __uint_as_float(v << 16); }
__device__ __forceinline__ float bf_hi(uint32_t v) { return __uint_as_float(v & 0xffff0000u); }
__device__ __forceinline__ float bfr(float v) { return __bfloat162float(__float2bfloat16_rn(v)); }
__device__ __forceinline__ float tanh_fast(float x) { float y; asm("tanh.approx.f32 %0, %1;" : "=f"(y) : "f"(x)); return y; }
__device__ __forceinline__ float ex2(float x) { float y; asm("ex2.approx.ftz.f32 %0, %1;" : "=f"(y) : "f"(x)); return y; }
__device__ __forceinline__ uint32_t hadd2u(uint32_t a, uint32_t b) { uint32_t r; asm("add.rn.f16x2 %0, %1, %2;" : "=r"(r) : "r"(a), "r"(b)); return r; }
__device__ __forceinline__ void ldsm2t(uint32_t a, uint32_t& r0, uint32_t& r1) {
  asm volatile("ldmatrix.sync.aligned.m8n8.x2.trans.shared.b16 {%0,%1}, [%2];" : "=r"(r0), "=r"(r1) : "r"(a) : "memory");
}
__device__ __forceinline__ uint32_t hfma2u(uint32_t a, uint32_t b, uint32_t c) { uint32_t r; asm("fma.rn.f16x2 %0, %1, %2, %3;" : "=r"(r) : "r"(a), "r"(b), "r"(c)); return r; }
__device__ __forceinline__ uint32_t badd2(uint32_t a, uint32_t b) { uint32_t r; asm("add.rn.bf16x2 %0, %1, %2;" : "=r"(r) : "r"(a), "r"(b)); return r; }
__device__ __forceinline__ uint32_t bmul2(uint32_t a, uint32_t b) { uint32_t r; asm("mul.rn.bf16x2 %0, %1, %2;" : "=r"(r) : "r"(a), "r"(b)); return r; }
__device__ __forceinline__ uint4 hadd8(uint4 a, uint4 b) { return make_uint4(hadd2u(a.x, b.x), hadd2u(a.y, b.y), hadd2u(a.z, b.z), hadd2u(a.w, b.w)); }
__device__ __forceinline__ float2 cexp_p(float lr, float wi, float p) {
  float m = ex2(lr * p), th = wi * p;
  return make_float2(m * __cosf(th), m * __sinf(th));
}
__device__ __forceinline__ float2 csq(float2 a) { return make_float2(fmaf(a.x, a.x, -a.y * a.y), (a.x + a.x) * a.y); }
__device__ __forceinline__ float2 cmul(float2 a, float2 b) { return make_float2(fmaf(a.x, b.x, -a.y * b.y), fmaf(a.x, b.y, a.y * b.x)); }
template <bool NEG> __device__ __forceinline__ void pmul(uint32_t re, uint32_t im, uint32_t y, uint32_t& ore, uint32_t& oim) {
  __half2 r = *reinterpret_cast<__half2*>(&re), i = *reinterpret_cast<__half2*>(&im), yy = *reinterpret_cast<__half2*>(&y);
  __half2 a = __hfma2(r, __low2half2(yy), __hneg2(__hmul2(i, __high2half2(yy))));
  __half2 b = NEG ? __hfma2(__hneg2(r), __high2half2(yy), __hneg2(__hmul2(i, __low2half2(yy)))) : __hfma2(r, __high2half2(yy), __hmul2(i, __low2half2(yy)));
  ore = *reinterpret_cast<uint32_t*>(&a); oim = *reinterpret_cast<uint32_t*>(&b);
}
struct Pow8 { uint32_t re[4], im[4]; float2 z2, z4, z6, z8; };
__device__ __forceinline__ Pow8 pow8(float2 z1) {
  Pow8 o;
  o.z2 = csq(z1); float2 z3 = cmul(o.z2, z1); o.z4 = csq(o.z2);
  float2 z5 = cmul(o.z4, z1), z7 = cmul(o.z4, z3); o.z6 = csq(z3); o.z8 = csq(o.z4);
  o.re[0] = pack_f16(1.f, z1.x); o.im[0] = pack_f16(0.f, z1.y); o.re[1] = pack_f16(o.z2.x, z3.x); o.im[1] = pack_f16(o.z2.y, z3.y);
  o.re[2] = pack_f16(o.z4.x, z5.x); o.im[2] = pack_f16(o.z4.y, z5.y); o.re[3] = pack_f16(o.z6.x, z7.x); o.im[3] = pack_f16(o.z6.y, z7.y);
  return o;
}
template <bool NEG> __device__ __forceinline__ void put_tile(uint32_t are, uint32_t aim, const Pow8& p, float2 y) {
  uint32_t r[4], i[4], yy = pack_f16(y.x, y.y);
#pragma unroll
  for (int k = 0; k < 4; k++) pmul<NEG>(p.re[k], p.im[k], yy, r[k], i[k]);
  sts128(are, r[0], r[1], r[2], r[3]); sts128(aim, i[0], i[1], i[2], i[3]);
}
__device__ __forceinline__ void mma_f16(float* c, uint32_t a0, uint32_t a1, uint32_t a2, uint32_t a3, uint32_t b0, uint32_t b1) {
  asm volatile("mma.sync.aligned.m16n8k16.row.col.f32.f16.f16.f32 {%0,%1,%2,%3}, {%4,%5,%6,%7}, {%8,%9}, {%0,%1,%2,%3};"
               : "+f"(c[0]), "+f"(c[1]), "+f"(c[2]), "+f"(c[3]) : "r"(a0), "r"(a1), "r"(a2), "r"(a3), "r"(b0), "r"(b1));
}
__device__ __forceinline__ void mma_bf16(float* c, uint32_t a0, uint32_t a1, uint32_t a2, uint32_t a3, uint32_t b0, uint32_t b1) {
  asm volatile("mma.sync.aligned.m16n8k16.row.col.f32.bf16.bf16.f32 {%0,%1,%2,%3}, {%4,%5,%6,%7}, {%8,%9}, {%0,%1,%2,%3};"
               : "+f"(c[0]), "+f"(c[1]), "+f"(c[2]), "+f"(c[3]) : "r"(a0), "r"(a1), "r"(a2), "r"(a3), "r"(b0), "r"(b1));
}
#define bar_arrive(id, n) asm volatile("bar.arrive " #id ", " #n ";" ::: "memory")
__device__ __forceinline__ void wgmma_ss_bf16_n224(float* d, uint64_t da, uint64_t db, int sd){
  asm volatile("{\n.reg .pred p;\nsetp.ne.b32 p, %114, 0;\nwgmma.mma_async.sync.aligned.m64n224k16.f32.bf16.bf16 {%0,%1,%2,%3,%4,%5,%6,%7,%8,%9,%10,%11,%12,%13,%14,%15,%16,%17,%18,%19,%20,%21,%22,%23,%24,%25,%26,%27,%28,%29,%30,%31,%32,%33,%34,%35,%36,%37,%38,%39,%40,%41,%42,%43,%44,%45,%46,%47,%48,%49,%50,%51,%52,%53,%54,%55,%56,%57,%58,%59,%60,%61,%62,%63,%64,%65,%66,%67,%68,%69,%70,%71,%72,%73,%74,%75,%76,%77,%78,%79,%80,%81,%82,%83,%84,%85,%86,%87,%88,%89,%90,%91,%92,%93,%94,%95,%96,%97,%98,%99,%100,%101,%102,%103,%104,%105,%106,%107,%108,%109,%110,%111}, %112, %113, p, 1, 1, 0, 1;\n}"
    : "+f"(d[0]),"+f"(d[1]),"+f"(d[2]),"+f"(d[3]),"+f"(d[4]),"+f"(d[5]),"+f"(d[6]),"+f"(d[7]),"+f"(d[8]),"+f"(d[9]),"+f"(d[10]),"+f"(d[11]),"+f"(d[12]),"+f"(d[13]),"+f"(d[14]),"+f"(d[15]),"+f"(d[16]),"+f"(d[17]),"+f"(d[18]),"+f"(d[19]),"+f"(d[20]),"+f"(d[21]),"+f"(d[22]),"+f"(d[23]),"+f"(d[24]),"+f"(d[25]),"+f"(d[26]),"+f"(d[27]),"+f"(d[28]),"+f"(d[29]),"+f"(d[30]),"+f"(d[31]),"+f"(d[32]),"+f"(d[33]),"+f"(d[34]),"+f"(d[35]),"+f"(d[36]),"+f"(d[37]),"+f"(d[38]),"+f"(d[39]),"+f"(d[40]),"+f"(d[41]),"+f"(d[42]),"+f"(d[43]),"+f"(d[44]),"+f"(d[45]),"+f"(d[46]),"+f"(d[47]),"+f"(d[48]),"+f"(d[49]),"+f"(d[50]),"+f"(d[51]),"+f"(d[52]),"+f"(d[53]),"+f"(d[54]),"+f"(d[55]),"+f"(d[56]),"+f"(d[57]),"+f"(d[58]),"+f"(d[59]),"+f"(d[60]),"+f"(d[61]),"+f"(d[62]),"+f"(d[63]),"+f"(d[64]),"+f"(d[65]),"+f"(d[66]),"+f"(d[67]),"+f"(d[68]),"+f"(d[69]),"+f"(d[70]),"+f"(d[71]),"+f"(d[72]),"+f"(d[73]),"+f"(d[74]),"+f"(d[75]),"+f"(d[76]),"+f"(d[77]),"+f"(d[78]),"+f"(d[79]),"+f"(d[80]),"+f"(d[81]),"+f"(d[82]),"+f"(d[83]),"+f"(d[84]),"+f"(d[85]),"+f"(d[86]),"+f"(d[87]),"+f"(d[88]),"+f"(d[89]),"+f"(d[90]),"+f"(d[91]),"+f"(d[92]),"+f"(d[93]),"+f"(d[94]),"+f"(d[95]),"+f"(d[96]),"+f"(d[97]),"+f"(d[98]),"+f"(d[99]),"+f"(d[100]),"+f"(d[101]),"+f"(d[102]),"+f"(d[103]),"+f"(d[104]),"+f"(d[105]),"+f"(d[106]),"+f"(d[107]),"+f"(d[108]),"+f"(d[109]),"+f"(d[110]),"+f"(d[111]) : "l"(da), "l"(db), "r"(sd));
}
__device__ __forceinline__ void wgmma_ss_bf16_n160(float* d, uint64_t da, uint64_t db, int sd){
  asm volatile("{\n.reg .pred p;\nsetp.ne.b32 p, %82, 0;\nwgmma.mma_async.sync.aligned.m64n160k16.f32.bf16.bf16 {%0,%1,%2,%3,%4,%5,%6,%7,%8,%9,%10,%11,%12,%13,%14,%15,%16,%17,%18,%19,%20,%21,%22,%23,%24,%25,%26,%27,%28,%29,%30,%31,%32,%33,%34,%35,%36,%37,%38,%39,%40,%41,%42,%43,%44,%45,%46,%47,%48,%49,%50,%51,%52,%53,%54,%55,%56,%57,%58,%59,%60,%61,%62,%63,%64,%65,%66,%67,%68,%69,%70,%71,%72,%73,%74,%75,%76,%77,%78,%79}, %80, %81, p, 1, 1, 0, 1;\n}"
    : "+f"(d[0]),"+f"(d[1]),"+f"(d[2]),"+f"(d[3]),"+f"(d[4]),"+f"(d[5]),"+f"(d[6]),"+f"(d[7]),"+f"(d[8]),"+f"(d[9]),"+f"(d[10]),"+f"(d[11]),"+f"(d[12]),"+f"(d[13]),"+f"(d[14]),"+f"(d[15]),"+f"(d[16]),"+f"(d[17]),"+f"(d[18]),"+f"(d[19]),"+f"(d[20]),"+f"(d[21]),"+f"(d[22]),"+f"(d[23]),"+f"(d[24]),"+f"(d[25]),"+f"(d[26]),"+f"(d[27]),"+f"(d[28]),"+f"(d[29]),"+f"(d[30]),"+f"(d[31]),"+f"(d[32]),"+f"(d[33]),"+f"(d[34]),"+f"(d[35]),"+f"(d[36]),"+f"(d[37]),"+f"(d[38]),"+f"(d[39]),"+f"(d[40]),"+f"(d[41]),"+f"(d[42]),"+f"(d[43]),"+f"(d[44]),"+f"(d[45]),"+f"(d[46]),"+f"(d[47]),"+f"(d[48]),"+f"(d[49]),"+f"(d[50]),"+f"(d[51]),"+f"(d[52]),"+f"(d[53]),"+f"(d[54]),"+f"(d[55]),"+f"(d[56]),"+f"(d[57]),"+f"(d[58]),"+f"(d[59]),"+f"(d[60]),"+f"(d[61]),"+f"(d[62]),"+f"(d[63]),"+f"(d[64]),"+f"(d[65]),"+f"(d[66]),"+f"(d[67]),"+f"(d[68]),"+f"(d[69]),"+f"(d[70]),"+f"(d[71]),"+f"(d[72]),"+f"(d[73]),"+f"(d[74]),"+f"(d[75]),"+f"(d[76]),"+f"(d[77]),"+f"(d[78]),"+f"(d[79]) : "l"(da), "l"(db), "r"(sd));
}
__device__ __forceinline__ void wgmma_rs_f16_n128(float* d, uint32_t a0, uint32_t a1, uint32_t a2, uint32_t a3, uint64_t db, int sd){
  asm volatile("{\n.reg .pred p;\nsetp.ne.b32 p, %69, 0;\nwgmma.mma_async.sync.aligned.m64n128k16.f32.f16.f16 {%0,%1,%2,%3,%4,%5,%6,%7,%8,%9,%10,%11,%12,%13,%14,%15,%16,%17,%18,%19,%20,%21,%22,%23,%24,%25,%26,%27,%28,%29,%30,%31,%32,%33,%34,%35,%36,%37,%38,%39,%40,%41,%42,%43,%44,%45,%46,%47,%48,%49,%50,%51,%52,%53,%54,%55,%56,%57,%58,%59,%60,%61,%62,%63}, {%64,%65,%66,%67}, %68, p, 1, 1, 0;\n}"
    : "+f"(d[0]),"+f"(d[1]),"+f"(d[2]),"+f"(d[3]),"+f"(d[4]),"+f"(d[5]),"+f"(d[6]),"+f"(d[7]),"+f"(d[8]),"+f"(d[9]),"+f"(d[10]),"+f"(d[11]),"+f"(d[12]),"+f"(d[13]),"+f"(d[14]),"+f"(d[15]),"+f"(d[16]),"+f"(d[17]),"+f"(d[18]),"+f"(d[19]),"+f"(d[20]),"+f"(d[21]),"+f"(d[22]),"+f"(d[23]),"+f"(d[24]),"+f"(d[25]),"+f"(d[26]),"+f"(d[27]),"+f"(d[28]),"+f"(d[29]),"+f"(d[30]),"+f"(d[31]),"+f"(d[32]),"+f"(d[33]),"+f"(d[34]),"+f"(d[35]),"+f"(d[36]),"+f"(d[37]),"+f"(d[38]),"+f"(d[39]),"+f"(d[40]),"+f"(d[41]),"+f"(d[42]),"+f"(d[43]),"+f"(d[44]),"+f"(d[45]),"+f"(d[46]),"+f"(d[47]),"+f"(d[48]),"+f"(d[49]),"+f"(d[50]),"+f"(d[51]),"+f"(d[52]),"+f"(d[53]),"+f"(d[54]),"+f"(d[55]),"+f"(d[56]),"+f"(d[57]),"+f"(d[58]),"+f"(d[59]),"+f"(d[60]),"+f"(d[61]),"+f"(d[62]),"+f"(d[63]) : "r"(a0), "r"(a1), "r"(a2), "r"(a3), "l"(db), "r"(sd));
}
__device__ __forceinline__ void wgmma_rs_f16_n96(float* d, uint32_t a0, uint32_t a1, uint32_t a2, uint32_t a3, uint64_t db, int sd){
  asm volatile("{\n.reg .pred p;\nsetp.ne.b32 p, %53, 0;\nwgmma.mma_async.sync.aligned.m64n96k16.f32.f16.f16 {%0,%1,%2,%3,%4,%5,%6,%7,%8,%9,%10,%11,%12,%13,%14,%15,%16,%17,%18,%19,%20,%21,%22,%23,%24,%25,%26,%27,%28,%29,%30,%31,%32,%33,%34,%35,%36,%37,%38,%39,%40,%41,%42,%43,%44,%45,%46,%47}, {%48,%49,%50,%51}, %52, p, 1, 1, 1;\n}"
    : "+f"(d[0]),"+f"(d[1]),"+f"(d[2]),"+f"(d[3]),"+f"(d[4]),"+f"(d[5]),"+f"(d[6]),"+f"(d[7]),"+f"(d[8]),"+f"(d[9]),"+f"(d[10]),"+f"(d[11]),"+f"(d[12]),"+f"(d[13]),"+f"(d[14]),"+f"(d[15]),"+f"(d[16]),"+f"(d[17]),"+f"(d[18]),"+f"(d[19]),"+f"(d[20]),"+f"(d[21]),"+f"(d[22]),"+f"(d[23]),"+f"(d[24]),"+f"(d[25]),"+f"(d[26]),"+f"(d[27]),"+f"(d[28]),"+f"(d[29]),"+f"(d[30]),"+f"(d[31]),"+f"(d[32]),"+f"(d[33]),"+f"(d[34]),"+f"(d[35]),"+f"(d[36]),"+f"(d[37]),"+f"(d[38]),"+f"(d[39]),"+f"(d[40]),"+f"(d[41]),"+f"(d[42]),"+f"(d[43]),"+f"(d[44]),"+f"(d[45]),"+f"(d[46]),"+f"(d[47]) : "r"(a0), "r"(a1), "r"(a2), "r"(a3), "l"(db), "r"(sd));
}
__device__ __forceinline__ void wgmma_rs_f16_n64(float* d, uint32_t a0, uint32_t a1, uint32_t a2, uint32_t a3, uint64_t db, int sd){
  asm volatile("{\n.reg .pred p;\nsetp.ne.b32 p, %37, 0;\nwgmma.mma_async.sync.aligned.m64n64k16.f32.f16.f16 {%0,%1,%2,%3,%4,%5,%6,%7,%8,%9,%10,%11,%12,%13,%14,%15,%16,%17,%18,%19,%20,%21,%22,%23,%24,%25,%26,%27,%28,%29,%30,%31}, {%32,%33,%34,%35}, %36, p, 1, 1, 1;\n}"
    : "+f"(d[0]),"+f"(d[1]),"+f"(d[2]),"+f"(d[3]),"+f"(d[4]),"+f"(d[5]),"+f"(d[6]),"+f"(d[7]),"+f"(d[8]),"+f"(d[9]),"+f"(d[10]),"+f"(d[11]),"+f"(d[12]),"+f"(d[13]),"+f"(d[14]),"+f"(d[15]),"+f"(d[16]),"+f"(d[17]),"+f"(d[18]),"+f"(d[19]),"+f"(d[20]),"+f"(d[21]),"+f"(d[22]),"+f"(d[23]),"+f"(d[24]),"+f"(d[25]),"+f"(d[26]),"+f"(d[27]),"+f"(d[28]),"+f"(d[29]),"+f"(d[30]),"+f"(d[31]) : "r"(a0), "r"(a1), "r"(a2), "r"(a3), "l"(db), "r"(sd));
}

struct Params {
  const __nv_bfloat16 *x, *logA, *aimag, *cre, *cim, *logdt, *dskip, *w1, *b1, *w2, *b2;
  __nv_bfloat16* out;
};

template <bool ALL>
__device__ __forceinline__ uint4 windows(uint32_t ac, uint32_t an, uint32_t o4, uint32_t o7, uint32_t o9) {
  const uint2 p = lds64(an - 8);
  const uint4 c = lds128(ac), n = lds128(an);
  const uint32_t w[9] = {p.x, p.y, c.x, c.y, c.z, c.w, n.x, n.y, n.z};
  uint32_t o[8], pe[8], s4[4], v5[4], v3[4];
#pragma unroll
  for (int i = ALL ? 0 : 1; i < 8; i++) { o[i] = __byte_perm(w[i], w[i + 1], 0x5432); pe[i] = hadd2u(w[i], o[i]); }
#pragma unroll
  for (int i = 2; i < 6; i++) { s4[i - 2] = hadd2u(pe[i - 1], pe[i]); v5[i - 2] = hadd2u(s4[i - 2], w[i + 1]); v3[i - 2] = hadd2u(o[i + 1], pe[i + 2]); }
  sts128(o4, v5[0], v5[1], v5[2], v5[3]);
  sts128(o4 + V3 - V5, v3[0], v3[1], v3[2], v3[3]);
  if (ALL) {
    uint32_t v7[4], v9[4];
#pragma unroll
    for (int i = 2; i < 6; i++) { uint32_t s6 = hadd2u(s4[i - 2], pe[i + 1]); v7[i - 2] = hadd2u(s6, o[i - 2]); v9[i - 2] = hadd2u(s6, hadd2u(pe[i - 2], w[i + 2])); }
    sts128(o7, v7[0], v7[1], v7[2], v7[3]);
    sts128(o9, v9[0], v9[1], v9[2], v9[3]);
  }
  return make_uint4(pe[4], pe[5], pe[6], pe[7]);
}
__device__ __forceinline__ uint32_t h2b(uint32_t h, float s) {
  float2 f = __half22float2(*reinterpret_cast<__half2*>(&h));
  return pack_bf16(f.x * s, f.y * s);
}
__device__ __forceinline__ uint32_t b2h(uint32_t b, float s) { return pack_f16(bf_lo(b) * s, bf_hi(b) * s); }

__global__ void __cluster_dims__(2, 1, 1) __launch_bounds__(384, 1)
fused_kernel(const __grid_constant__ CUtensorMap tm_x, const __grid_constant__ CUtensorMap tm_w1,
             const __grid_constant__ CUtensorMap tm_w2, const Params P) {
  extern __shared__ __align__(1024) uint8_t smem_raw[];
  const uint32_t sb = smem_u32(smem_raw);
  const int tid = threadIdx.x, wid = __shfl_sync(~0u, tid >> 5, 0), wg = wid >> 2, warp = wid & 3, lane = tid & 31, g = lane >> 2, q = lane & 3;
  const int bid = blockIdx.x, srank = bid & 1, cblk = (bid >> 1) & 3, iblk = bid >> 3, jblk = 4 * srank + cblk;
  const int kch = bid * 5 + (wg == 2 ? 4 : wid >> 1), pidx = kch * 64 + ((wg == 2 ? wid >> 1 : wid) & 1) * 32 + lane;
  uint32_t pA = ldg32(P.logA + 2 * pidx), pI = ldg32(P.aimag + 2 * pidx), pR = ldg32(P.cre + 2 * pidx), pC = ldg32(P.cim + 2 * pidx);
  const uint32_t pdt = ldg16(P.logdt + kch);
  unsigned ep;
  asm volatile("ld.global.b32 %0, [%1];" : "=r"(ep) : "l"(g_epoch + bid));
  const int own = (7 * cblk) >> 1, blk1 = 14 * srank + own, hb1 = 12 + 14 * ((jblk - 1) >> 1) + ((jblk - 1) & 1);
  const bool has_half = jblk != 0 && jblk != 7;
  const int blk2 = (5 * cblk + 1) >> 1, hb2 = 5 * cblk + ((cblk & 1) ? 0 : 4);
  auto bar = [&](int i) { return sb + BAR + 8 * i; };
  auto load1 = [&](int kc) {
    uint32_t fb = bar(B_FULL1 + kc % 3), dst = sb + (kc % 3) * S1_STAGE;
    mbar_expect(fb, has_half ? S1_STAGE : S1_STAGE - 8192);
    tma2d(dst, &tm_x, kc * 64, iblk * 128, fb);
#pragma unroll 1
    for (int b = 0; b < 3; b++) tma2d(dst + S1_B + b * 8192, &tm_w1, (blk1 + b) * 64, kc * 64, fb);
    if (has_half) tma2d(dst + S1_B + 24576, &tm_w1, hb1 * 32, kc * 64, fb);
  };
  if (wid == 0) {
    if (elect()) {
      TLREC(0); TLGT(62);
      if (sb & 1023) __trap();
      for (int i = 0; i < 17; i++) mbar_init(bar(i), 1);
      mbar_init(bar(B_EPI1), 128); mbar_init(bar(B_C8), 2);
      asm volatile("fence.mbarrier_init.release.cluster;" ::: "memory");
#pragma unroll 1
      for (int kc = 0; kc < 2; kc++) load1(kc);
      mbar_expect(bar(B_XCH), 20480);
    }
    __syncwarp();
  } else if (wid == 1) sts32(sb + REL + lane * 4, 0);
  asm volatile("barrier.cluster.arrive.relaxed.aligned;" ::: "memory");
  uint4 xr[10];
  uint32_t pb1 = 0, pb2 = 0, pdsk = 0;
  float mean = 0.f;
  if (wg == 2) {
    uint4 wr[10];
    const int t = tid & 127;
    const __nv_bfloat16* px = P.x + (iblk * 128 + jblk * 16 + (warp & 1) * 8 + g) * D + (warp >> 1) * 320 + q * 8;
    const __nv_bfloat16* pw = P.w1 + (iblk * 40 + warp * 10) * F + jblk * 216 + min(lane, 26) * 8;
#pragma unroll
    for (int i = 1; i < 10; i++) xr[i] = ldg128(px + i * 32);
#pragma unroll
    for (int r = 0; r < 10; r++) wr[r] = ldg128(pw + r * F);
    pdsk = ldg16(P.dskip + bid * 5 + min(lane, 4));
    pb1 = ldg32(P.b1 + (t < 96 ? blk1 * 64 + 2 * t : (has_half ? hb1 : 0) * 32 + (2 * t & 31)));
    pb2 = ldg32(P.b2 + (t < 64 ? blk2 * 64 + 2 * t : hb2 * 32 + (2 * t & 31)));
    xr[0] = ldg128(px);
    const uint32_t ONE = 0x3f803f80u, sel = (q == (g >> 1)) ? ((g & 1) ? 0x3f800000u : 0x00003f80u) : 0u;
    float c0[4] = {0, 0, 0, 0}, c1[4] = {0, 0, 0, 0}, c2[4] = {0, 0, 0, 0}, c3[4] = {0, 0, 0, 0};
#pragma unroll
    for (int i = 0; i < 10; i += 2) {
      mma_bf16(c0, xr[i].x, xr[i].y, xr[i].z, xr[i].w, ONE, ONE);
      mma_bf16(c1, xr[i + 1].x, xr[i + 1].y, xr[i + 1].z, xr[i + 1].w, ONE, ONE);
    }
    float s = (c0[0] + c0[2]) + (c1[0] + c1[2]);
    sts32f(sb + LS1 + warp * 32 + g * 4, s);
    bar_sync(1, 128);
    mean = bfr((s + lds32f(sb + LS1 + (warp ^ 2) * 32 + g * 4)) * (1.f / D));
    const uint32_t nm = pack_bf16(-mean, -mean);
#pragma unroll
    for (int i = 0; i < 4; i++) c0[i] = c1[i] = 0.f;
#pragma unroll
    for (int i = 0; i < 10; i++) {
      xr[i] = make_uint4(badd2(xr[i].x, nm), badd2(xr[i].y, nm), badd2(xr[i].z, nm), badd2(xr[i].w, nm));
      mma_bf16(c0, xr[i].x, ONE, xr[i].y, ONE, xr[i].x, xr[i].y);
      mma_bf16(c1, xr[i].z, ONE, xr[i].w, ONE, xr[i].z, xr[i].w);
    }
    if (sel) sts64f(sb + LS2 + warp * 64 + g * 8, (g & 1) ? c0[1] + c1[1] : c0[0] + c1[0], (g & 1) ? c0[3] + c1[3] : c0[2] + c1[2]);
#pragma unroll
    for (int i = 0; i < 10; i += 2) {
      mma_bf16(c2, wr[i].x, wr[i].y, wr[i + 1].x, wr[i + 1].y, sel, sel);
      mma_bf16(c3, wr[i].z, wr[i].w, wr[i + 1].z, wr[i + 1].w, sel, sel);
    }
    if (lane < 27) {
      sts128f(sb + CSS + warp * 864 + lane * 32, c2[0], c2[1], c2[2], c2[3]);
      sts128f(sb + CSS + warp * 864 + lane * 32 + 16, c3[0], c3[1], c3[2], c3[3]);
    }
    if (t == 0) TLREC(43);
  }
  {
    const uint32_t tb = sb + (wg == 2 ? TB2 + warp * TB_SZ : TBG + wid * TB_SZ), tw = tb + lane * 16, tr = tb + (lane >> 3) * 512 + (lane & 7) * 16;
    const uint32_t ca = pR & 0x7fff7fffu, cb = pC & 0x7fff7fffu;
    unsigned e = __reduce_max_sync(~0u, max(max(ca, cb), max(ca << 16, cb << 16))) >> 23;
    e = min(max(e, 1u), 252u);
    const float sc = __uint_as_float((253u - e) << 23), dt = bfr(expf(bf_lo(pdt)));
    if (wid >= 8 && (wid & 1)) { pA >>= 16; pI >>= 16; pR >>= 16; pC >>= 16; }
    if (tid == 0) TLREC(40);
    float acc[5][4], fl = 0.f;
#pragma unroll
    for (int i = 0; i < 5; i++) acc[i][0] = acc[i][1] = acc[i][2] = acc[i][3] = 0.f;
#pragma unroll 1
    for (int rd = wg >> 1; rd < 2; rd++) {
      const float lr = -bfr(expf(bf_lo(pA))) * dt * 1.4426950408889634f, wi = bf_lo(pI) * dt;
      const float2 C = make_float2(bf_lo(pR) * sc, bf_lo(pC) * sc);
      pA >>= 16; pI >>= 16; pR >>= 16; pC >>= 16;
      const float2 Z = cexp_p(lr, wi, 128.f);
      const Pow8 s = pow8(cexp_p(lr, wi, 1.f));
      sts128(tw + 4 * 512, s.re[0], s.re[1], s.re[2], s.re[3]); sts128(tw + 5 * 512, s.im[0], s.im[1], s.im[2], s.im[3]);
      put_tile<false>(tw + 6 * 512, tw + 7 * 512, s, Z);
      const Pow8 a = pow8(s.z8);
      put_tile<true>(tw, tw + 2 * 512, a, C);
      put_tile<true>(tw + 512, tw + 3 * 512, a, cmul(C, a.z8));
      const Pow8 w = pow8(Z);
      put_tile<false>(tw + 12 * 512, tw + 13 * 512, w, w.z8);
      const uint32_t y2 = pack_f16(s.z2.x, s.z2.y), y4 = pack_f16(s.z4.x, s.z4.y), y6 = pack_f16(s.z6.x, s.z6.y);
      uint32_t r[3], i[3];
      pmul<false>(w.re[1], w.im[1], y2, r[0], i[0]); pmul<false>(w.re[1], w.im[1], y4, r[1], i[1]); pmul<false>(w.re[1], w.im[1], y6, r[2], i[2]);
      sts128(tw + 8 * 512, w.re[1], r[0], r[1], r[2]); sts128(tw + 9 * 512, w.im[1], i[0], i[1], i[2]);
      pmul<false>(w.re[2], w.im[2], y4, r[0], i[0]); pmul<false>(w.re[3], w.im[3], y4, r[1], i[1]);
      sts128(tw + 10 * 512, w.re[2], w.re[3], r[0], r[1]); sts128(tw + 11 * 512, w.im[2], w.im[3], i[0], i[1]);
      const float2 zl = csq(w.z8);
      fl = fmaf(C.x, zl.x, fmaf(-C.y, zl.y, fl));
      __syncwarp();
#pragma unroll
      for (int j = 0; j < 4; j++) {
        uint32_t a0, a1, a2, a3, b[10];
        ldsm4t(tr + j * 128, a0, a1, a2, a3);
        ldsm4t(tr + j * 128 + 2048, b[0], b[1], b[2], b[3]);
        ldsm4t(tr + j * 128 + 4096, b[4], b[5], b[6], b[7]);
        ldsm2t(tr + j * 128 + 6144, b[8], b[9]);
#pragma unroll
        for (int k = 0; k < 5; k++) mma_f16(acc[k], a0, a1, a2, a3, b[2 * k], b[2 * k + 1]);
      }
      __syncwarp();
    }
    const uint32_t ps = sb + PS + wid * PS_SZ;
#pragma unroll
    for (int i = 0; i < 5; i++) {
      sts64f(ps + i * 512 + lane * 8, acc[i][0], acc[i][1]);
      sts64f(ps + i * 512 + 256 + lane * 8, acc[i][2], acc[i][3]);
    }
#pragma unroll
    for (int o = 16; o; o >>= 1) fl += __shfl_xor_sync(~0u, fl, o);
    sts64f(ps + 2560, fl, 2.f * dt * __uint_as_float((e + 1u) << 23));
    if (tid == 0) TLREC(41);
    if (tid == 256) TLREC(42);
  }

  if (wg == 2) {
    const int t = tid & 127;
    bar_arrive(4, 384);
    bar_sync(1, 128);
      const uint2 u0 = lds64(sb + LS2 + warp * 64 + g * 8), u1 = lds64(sb + LS2 + (warp ^ 2) * 64 + g * 8);
      const float dl = (__uint_as_float(u0.y) + __uint_as_float(u1.y)) * (1.f / D);
      const float var = fmaxf((__uint_as_float(u0.x) + __uint_as_float(u1.x)) * (1.f / D) - dl * dl, 0.f);
      const float rs = rstd(var), r2 = rstd(var * rs * rs);
      if (warp < 2) sts64f(sb + LS1 + warp * 64 + g * 8, rs * r2, -(mean * rs + bfr(dl * rs)) * r2);
      else if (t < 118) {
        const uint32_t ca = sb + CSS + (t - 64) * 16;
        float4 a = lds128f(ca), b = lds128f(ca + 864), c = lds128f(ca + 1728), d = lds128f(ca + 2592);
        sts128f(ca, (a.x + b.x) + (c.x + d.x), (a.y + b.y) + (c.y + d.y), (a.z + b.z) + (c.z + d.z), (a.w + b.w) + (c.w + d.w));
      }
      const uint32_t la = sb + LNT + ((warp >> 1) * 320 + (lane & 6) * 4 + (lane >> 3) * 2 + (lane & 1)) * 32 + (warp & 1) * 16;
#pragma unroll
      for (int i = 0; i < 10; i++) stsm4t(la + i * 1024, b2h(xr[i].x, rs), b2h(xr[i].y, rs), b2h(xr[i].z, rs), b2h(xr[i].w, rs));
      fence_async_smem();
  }
  int role;
  asm volatile("shfl.sync.idx.b32 %0, %1, 0, 31, 0xffffffff;" : "=r"(role) : "r"(tid >> 8));
  if (role) {
    const int t = tid & 127;
    {
      bar_sync(5, 384);
      if (t == 0) {
        bulk_store(g_xnT + (iblk * 8 + jblk) * 10240, sb + LNT, 20480);
        bulk_store(g_stats + iblk * 128 + jblk * 16, sb + LS1, 128);
        bulk_store(g_cs + iblk * F + jblk * 216, sb + CSS, 864);
        bulk_commit();
        asm volatile("cp.async.bulk.prefetch.L2.global [%0], %1;" ::"l"(P.w2 + bid * 8640), "r"(17280) : "memory");
        TLREC(44);
      }
    }
    ep++;
    {
#pragma unroll
      for (int i = 0; i < 10; i++) sts128(sb + KA + min(t + i * 128, 5 * KA_SZ / 16 - 1) * 16, 0, 0, 0, 0);
      bar_sync(1, 128);
      const int a = t >> 3, c = t & 7;
      const int y2 = (543 - 256 - 128 * (c & 1) - (c & 6) - 8 * a) * 2;
      const int y3 = 95 - ((16 * (c & 3) + a - 1 + (c >> 2)) & 63), y4 = 63 - ((8 * c + (a >> 1) - 1 + (a & 1)) & 63);
      const int o3 = KA_4 + (c >> 2) * 4, o4 = KA_8 + (a & 1) * 4;
      uint32_t ps = sb + PS + t * 4;
#pragma unroll 1
      for (int ch = 0; ch < 5; ch++) {
        float v[6] = {0, 0, 0, 0, 0, 0}, mx = 0.f;
#pragma unroll 1
        for (int i = ch == 4 ? 4 : 2; i; i--, ps += PS_SZ) {
          const uint2 tl = lds64(ps - t * 4 + 2560);
          const float us = __uint_as_float(tl.y);
#pragma unroll
          for (int k = 0; k < 5; k++) v[k] = fmaf(lds32f(ps + k * 512), us, v[k]);
          v[5] = fmaf(__uint_as_float(tl.x), us, v[5]);
          mx = fmaxf(mx, us);
        }
        if (ch == 2 && t == 0) { TLREC(45); bulk_wait<0>(); TLREC(46); red_relaxed(&g_cnt[CNT_PREP * 32]); }
        const float dd = bf_lo(__shfl_sync(~0u, pdsk, ch));
        const unsigned e = min(__float_as_uint(fmaxf(mx, fabsf(dd) * (1.f / 64))) >> 23, 240u);
        const float inv = __uint_as_float((246u - e) << 23);
        const uint32_t k0 = sb + KA + ch * KA_SZ;
        if (t == 0) {
          const uint32_t h = pack_f16(v[3] * inv, v[3] * inv);
          sts16(k0 + 58, h); sts32(k0 + 60, h); sts16(k0 + 64, h); sts64(k0 + KA_C1 + 56, h, h);
          sts64(sb + SCL + ch * 8, (e + 8u) << 23, pack_f16(v[4] * inv, v[4] * inv));
          v[0] += dd; v[3] = v[4]; v[4] = v[5];
        }
        const uint32_t h01 = pack_f16(v[0] * inv, v[1] * inv), h2 = pack_f16(v[2] * inv, 0.f), h34 = pack_f16(v[3] * inv, v[4] * inv);
        auto put = [&](int yb, unsigned short h) { sts16(k0 + yb, h); sts16(k0 + KA_C1 - 2 + yb, h); };
        auto putf = [&](int o, int y, unsigned short h) {
          sts16(k0 + o + (y >> 1) * 8 + (y & 1) * 2, h); sts16(k0 + KA_C1 + o + ((y - 1) >> 1) * 8 + ((y - 1) & 1) * 2, h);
        };
        put((543 - t) * 2, h01); put((415 - t) * 2, h01 >> 16); put(y2, h2);
        if (!(c & 2)) { put(y2 - 2, h2); put(t ? y2 + 2 : y2, h2); }
        putf(o3, y3, h34); putf(o4, y4, h34 >> 16);
      }
    }
    if (t == 0) TLREC(20);
    bar_sync(1, 128);
    sts128(sb + (t < 80 ? UU + (t >> 3) * U_H + (t & 7) * 16 : t < 112 ? V5 + (t & 16) * 208 + (t & 15) * 16 : V9 + 1024), 0, 0, 0, 0);
    sts128(sb + (t < 64 ? P4 + t * 16 : P8 + (t >> 5) * P8_H + (t & 31) * 16), 0, 0, 0, 0);
    sts128(sb + P4 + 4096 + t * 16, 0, 0, 0, 0);
    if (t < 64) sts128(sb + PD + (2 + (t >> 5)) * PD_H + (t & 31) * 16, 0, 0, 0, 0);
    if (t == 0) { TLREC(21); poll_acquire(&g_cnt[CNT_PREP * 32], ep * 128); TLREC(22); }
    bar_sync(1, 128);
    if (t < 120) {
      const int b = (t * 6554) >> 16, p = t - b * 10;
      const uint32_t dst = sb + UU + p * U_H + (8 + b) * 16;
      const __half* src = g_xnT + b * 10240 + bid * 80 + p * 8;
#pragma unroll
      for (int i = 0; i < 11; i++)
        if (i < 10 || t < 80) asm volatile("cp.async.cg.shared.global [%0], [%1], 16;" ::"r"(dst + i * 192), "l"(src + i * 122880) : "memory");
    }
    {
      const float2 st = __ldcg(&g_stats[iblk * 128 + t]);
      const float* pc = g_cs + (t < 96 ? blk1 * 64 + 2 * t : (has_half ? hb1 : 0) * 32 + (2 * t & 31));
      float2 s = make_float2(0.f, 0.f);
#pragma unroll
      for (int i = 0; i < 16; i++) { float2 v = __ldcg(reinterpret_cast<const float2*>(pc + i * F)); s.x += v.x; s.y += v.y; }
      if (t < 112) sts128f(sb + CSB + t * 16, 0.5f * s.x, 0.5f * bf_lo(pb1), 0.5f * s.y, 0.5f * bf_hi(pb1));
      if (t < 80) sts64f(sb + EP2 + (t >> 3) * 64 + (t & 3) * 16 + (t & 4) * 2, 0.5f * bf_lo(pb2), 0.5f * bf_hi(pb2));
      sts64f(sb + RST + t * 8, st.x, st.y);
      mbar_arrive(bar(B_EPI1));
      if (t == 0) TLREC(47);
    }
    asm volatile("cp.async.wait_all;" ::: "memory");
    bar_sync(1, 128);
    if (t == 0) TLREC(23);
    {
      float aD[64];
#pragma unroll
      for (int i = 0; i < 64; i++) aD[i] = 0.f;
      uint4 p2n = make_uint4(0, 0, 0, 0);
      const uint32_t hi = warp >> 1, par = (t & 1), srow = ((lane >> 3) * 16 + (warp & 1) * 8 + (lane & 7)) * 16;
      const uint32_t kcp = sb + KA + ((g & 1) ? 0 : KA_C1), kw = q - (warp & 1) * 4;
      uint32_t kd = kcp + 4 * (((415 - g) >> 1) - 136 * hi + kw), kf = kcp + KA_4 + 8 * (((63 - g) >> 1) - 24 * hi + kw);
      uint32_t un = sb + UU + par * U_H + (8 + (t >> 1)) * 16;
      uint4* yo = reinterpret_cast<uint4*>(g_yc) + (((t >> 4) * 2 + (t & 1)) * 640 + bid * 5 - 1) * 8;
      auto finish = [&](int ch, const uint4& p2) {
          const uint2 sc = lds64(sb + SCL - 8 + ch * 8);
          const uint32_t rd = sb + PD + par * PD_H + (t >> 1) * 16, r4 = sb + P4 + t * 16, r8 = sb + P8 + par * P8_H + (t >> 1) * 16;
          const float os = __uint_as_float(sc.x);
          const uint32_t xo = ((t >> 1) ^ (bid * 5 + ch - 1)) & 7;
          uint4 y = hadd8(hadd8(lds128(rd + 272), lds128(rd + 2 * PD_H)), hadd8(lds128(r4), lds128(r4 + 4096)));
          yo[xo] = make_uint4(h2b(y.x, os), h2b(y.y, os), h2b(y.z, os), h2b(y.w, os));
          y = hadd8(hadd8(lds128(rd + 272 + 1024), lds128(rd + 2 * PD_H + 1024)), hadd8(lds128(r4 + 2048), lds128(r4 + 4096 + 2048)));
          uint4 z = hadd8(lds128(r8 + 512), lds128(r8 + 2 * P8_H));
          y = hadd8(y, make_uint4(hfma2u(p2.x, sc.y, z.x), hfma2u(p2.y, sc.y, z.y), hfma2u(p2.z, sc.y, z.z), hfma2u(p2.w, sc.y, z.w)));
          yo[16 * 640 * 8 + xo] = make_uint4(h2b(y.x, os), h2b(y.y, os), h2b(y.z, os), h2b(y.w, os));
          if (t == 0) TLREC(23 + ch);
        };
#pragma unroll 1
      for (int ch = 0;; ch++) {
        const uint4 p2 = p2n;
        if (ch < 5) {
          const uint32_t uc = par ? un - U_H : un + U_H - 16;
          p2n = windows<true>(uc, un, sb + V5 + 256 + t * 16, sb + V7 + (par ^ 1) * 1024 + (t >> 1) * 16, sb + V9 + par * 1024 + ((t + 1) >> 1) * 16);
          if (warp < 2) windows<false>(uc + 1024, un + 1024, sb + V5 + 256 + 2048 + t * 16, 0, 0);
        }
        wg_wait<0>();
        reg_pin<64>(aD);
        {
          uint32_t pk[16];
          pk[0] = pack_f16(aD[0], aD[1]);
#pragma unroll
          for (int j = 1; j < 16; j++) pk[j] = pack_f16(aD[4 * j] + aD[4 * j - 2], aD[4 * j + 1] + aD[4 * j - 1]);
          const uint32_t pa = sb + PD + warp * PD_H + 272 + lane * 16;
#pragma unroll
          for (int j = 0; j < 16; j += 4) stsm4t(pa + j * 128, pk[j], pk[j + 1], pk[j + 2], pk[j + 3]);
        }
        fence_async_smem();
        bar_sync(1, 128);
        if (ch == 5) break;
        float a4[48], a8[32];
        {
          uint2 f[10];
#pragma unroll
          for (int i = 0; i < 10; i++) f[i] = lds64(i < 6 ? kf + 32 * i : kf + hi * 64 + 384 + 32 * (i - 6));
          const uint64_t d4 = mkdesc(sb + V5, V3 - V5, 256, 0), d8 = mkdesc(sb + V9, V7 - V9, 256, 0);
          wg_fence();
#pragma unroll
          for (int m = 0; m < 4; m++) wgmma_rs_f16_n96(a4, m > 1 ? f[m + 2].x : 0u, f[m].x, m > 1 ? f[m + 2].y : 0u, f[m].y, d4 + m * 8, m);
#pragma unroll
          for (int m = 0; m < 2; m++) wgmma_rs_f16_n64(a8, f[m + 8].x, f[m + 6].x, f[m + 8].y, f[m + 6].y, d8 + m * 8, m);
          wg_commit();
        }
        if (ch) finish(ch, p2);
        wg_wait<0>();
        reg_pin<48>(a4); reg_pin<32>(a8);
        bar_sync(1, 128);
        {
          uint32_t pk[12];
          pk[0] = pack_f16(a4[0], a4[1]);
#pragma unroll
          for (int j = 1; j < 12; j++) pk[j] = pack_f16(a4[4 * j] + a4[4 * j - 2], a4[4 * j + 1] + a4[4 * j - 1]);
          const uint32_t pa = sb + P4 + 1024 + hi * 4864 + srow;
#pragma unroll
          for (int j = 0; j < 12; j += 4) stsm4(pa + j * 256, pk[j], pk[j + 1], pk[j + 2], pk[j + 3]);
#pragma unroll
          for (int h = 0; h < 2; h++) {
            pk[0] = pack_f16(a8[16 * h], a8[16 * h + 1]);
#pragma unroll
            for (int j = 1; j < 4; j++) pk[j] = pack_f16(a8[16 * h + 4 * j] + a8[16 * h + 4 * j - 2], a8[16 * h + 4 * j + 1] + a8[16 * h + 4 * j - 1]);
            stsm4(sb + P8 + 512 + (2 * hi + 1 - h) * P8_H + srow, pk[0], pk[1], pk[2], pk[3]);
          }
        }
        {
          uint32_t f[34];
#pragma unroll
          for (int i = 0; i < 34; i++) f[i] = lds32(kd - 256 + 16 * i);
          const uint64_t du = mkdesc(sb + UU + ch * 2 * U_H, U_H, 128, 0);
          wg_fence();
#pragma unroll
          for (int m = 0; m < 9; m++) wgmma_rs_f16_n128(aD, m ? f[16 + 2 * m] : 0u, f[2 * m], m ? f[17 + 2 * m] : 0u, f[2 * m + 1], du + m, m);
          wg_commit();
        }
        kd += KA_SZ; kf += KA_SZ; un += 2 * U_H; yo += 8;
      }
      finish(5, p2n);
      fence_async_smem();
      bar_sync(1, 128);
    }
    asm volatile("barrier.cluster.wait.acquire.aligned;" ::: "memory");
    if (t == 0) {
      red_release(&g_cnt[(CNT_CONV + (bid >> 5)) * 32]);
      TLREC(30);
      mbar_expect(bar(B_YC), 20480);
      poll_acquire(&g_cnt[(CNT_CONV + cblk) * 32], ep * 32);
      fence_async_all();
      TLREC(31);
      bulk_load(sb + YC, g_yc + ((iblk * 2 + srank) * 640 + cblk * 160) * 64, 20480, bar(B_YC));
    }
  } else {
    fence_async_smem();
    bar_arrive(5, 384);
    float acc1[112];
#pragma unroll
    for (int i = 0; i < 112; i++) asm volatile("mov.b32 %0, 0;" : "=f"(acc1[i]));
    bar_sync(4, 384);
    const bool leader = elect();
    ep++;
    __nv_bfloat16* hrow = g_h + (iblk * 2 + wg) * 54 * 2048;
    auto krow = [&](int m) {
      const int j = (m * 43) >> 7, k = m < 3 ? own + m : m < 12 ? ((7 * ((cblk + m - 3 * j + 1) & 3)) >> 1) + j - 1 : 6;
      return m == 13 ? 26 + srank : 28 * srank + 2 * k;
    };
    unsigned* hcnt = &g_cnt[(CNT_H + (iblk * 4 + srank * 2 + wg) * 3) * 32];
    auto load2a = [&](int m) {
      uint32_t fb = bar(B_FULLA + wg * 4 + (m & 3));
      mbar_expect(fb, 8192);
      bulk_load(sb + S2_A + (m & 3) * 16384 + wg * 8192, hrow + krow(m) * 2048, 8192, fb);
    };
    auto slotb = [&](int sl) { return sb + (sl ? (sl - 1) * S2_BSZ : S2_B0); };
    auto load2b = [&](int m) {
      uint32_t fb = bar(B_FULLB + m % 3), dst = slotb(m % 3);
      mbar_expect(fb, S2_BSZ);
      const int r = krow(m) * 32;
      tma2d(dst, &tm_w2, blk2 * 64, r, fb);
      tma2d(dst + 8192, &tm_w2, blk2 * 64 + 64, r, fb);
      tma2d(dst + 16384, &tm_w2, hb2 * 32, r, fb);
    };
    {
      float* acc = acc1;
#pragma unroll 1
      for (int kc = 0; kc < 10; kc++) {
        int st = kc % 3;
        mbar_wait(bar(B_FULL1 + st), (kc / 3) & 1);
        if (wid == 0 && leader) TLREC(50 + kc);
        uint64_t da = mkdesc(sb + st * S1_STAGE + wg * 8192, 16, 1024, 1), db = mkdesc(sb + st * S1_STAGE + S1_B, 8192, 1024, 1);
        wg_fence();
#pragma unroll
        for (int k = 0; k < 4; k++) wgmma_ss_bf16_n224(acc, da + k * 2, db + k * 128, 1);
        wg_commit();
        wg_wait<1>();
        if (warp == 1 && leader) {
          if (kc == 9) mbar_arrive(bar(B_C8));
          if (kc != 8 && last_of_two(sb + REL + kc * 4)) { if (kc < 8) load1(kc + 2); else load2b(0); }
        }
        __syncwarp();
      }
      wg_wait<0>();
      reg_pin<112>(acc);
      if (warp == 1 && leader) {
        TLREC(2 + wg * 8);
        if (last_of_two(sb + REL + 8 * 4)) { load2b(1); load2b(2); }
      }
      __syncwarp();
      mbar_wait(bar(B_EPI1), 0);
      mbar_wait(bar(B_C8), 0);
      const uint2 s0 = lds64(sb + RST + (wid * 16 + g) * 8), s1 = lds64(sb + RST + (wid * 16 + g + 8) * 8);
      const float a0 = 0.5f * __uint_as_float(s0.x), a1 = 0.5f * __uint_as_float(s1.x), b0 = __uint_as_float(s0.y), b1 = __uint_as_float(s1.y);
      const uint32_t hw = sb + S2_A + wg * 8192 + warp * 1024, ha = hw + ((lane & 15) ^ (srank * 8)) * 64, hx = (lane >> 4) ^ ((lane >> 1) & 3);
      const uint32_t hoff = HALF - S2_A - wg * 4096;
      auto gelu = [](float hv) {
        return fmaf(hv, tanh_fast(hv * fmaf(hv * hv, 0.2854192648f, 1.5957691216f)), hv);
      };
      uint32_t pk[4];
#pragma unroll
      for (int n = 0; n < 28; n++) {
        float4 cb = lds128f(sb + CSB + n * 64 + q * 16);
        float v0 = fmaf(a0, acc[n * 4], fmaf(b0, cb.x, cb.y)), v1 = fmaf(a0, acc[n * 4 + 1], fmaf(b0, cb.z, cb.w));
        float v2 = fmaf(a1, acc[n * 4 + 2], fmaf(b1, cb.x, cb.y)), v3 = fmaf(a1, acc[n * 4 + 3], fmaf(b1, cb.z, cb.w));
        pk[(n & 1) * 2] = pack_bf16(gelu(v0), gelu(v1));
        pk[(n & 1) * 2 + 1] = pack_bf16(gelu(v2), gelu(v3));
        if (n & 1) stsm4(ha + (n < 24 ? (n >> 3) * 16384 + (n & 4) * 1024 : hoff) + ((hx ^ (n & 2)) << 4), pk[0], pk[1], pk[2], pk[3]);
        if (n == 7 || n == 15 || n == 27) {
          fence_async_smem();
          __syncwarp();
          if (leader) {
            const int b = n < 16 ? n >> 3 : 2;
            bulk_store(hrow + (blk1 + b) * 4096 + warp * 512, hw + b * 16384, 1024);
            bulk_store(hrow + (blk1 + b) * 4096 + 2048 + warp * 512, hw + b * 16384 + 4096, 1024);
            if (n == 27 && has_half) bulk_store(hrow + hb1 * 2048 + warp * 512, hw + hoff, 1024);
            bulk_commit();
            if (b) { bulk_wait<1>(); red_relaxed(hcnt + (b - 1) * 32); }
            if (wid == 0) TLREC(32 + b);
          }
          __syncwarp();
        }
      }
      if (wg) bar_sync(3, 128); else bar_sync(2, 128);
      if (warp == 0 && leader) TLREC(3 + wg * 8);
    }
    asm volatile("barrier.cluster.wait.acquire.aligned;" ::: "memory");
    float acc[80];
    const uint64_t da0 = mkdesc(sb + S2_A + wg * 8192, 16, 512, 2);
#pragma unroll
    for (int m = 0; m < 3; m++) {
      mbar_wait(bar(B_FULLB + m), 0);
      const uint64_t db = mkdesc(slotb(m), 8192, 1024, 1);
      wg_fence();
#pragma unroll
      for (int k = 0; k < 4; k++) wgmma_ss_bf16_n160(acc, da0 + m * 1024 + (k >> 1) * 256 + (k & 1) * 2, db + k * 128, m | k);
      wg_commit();
    }
    if (warp == 0 && leader) {
      poll_acquire(hcnt, ep * 16);
      fence_async_all();
      load2a(3);
      TLREC(18 + wg);
    }
    __syncwarp();
    wg_wait<2>();
    if (warp == 0 && leader) load2a(4);
    if (warp == 1 && leader && last_of_two(sb + REL + 10 * 4)) load2b(3);
    __syncwarp();
    wg_wait<1>();
    if (warp == 0 && leader) load2a(5);
    if (warp == 1 && leader && last_of_two(sb + REL + 11 * 4)) load2b(4);
    if (leader) { bulk_wait<0>(); red_relaxed(hcnt + 64); if (warp == 0) TLREC(4 + wg * 8); }
    __syncwarp();
    if (wg) bar_sync(3, 128); else bar_sync(2, 128);
#pragma unroll 1
    for (int m = 3; m < 13; m++) {
      int sl = m % 3;
      mbar_wait(bar(B_FULLB + sl), (m / 3) & 1);
      mbar_wait(bar(B_FULLA + wg * 4 + (m & 3)), ((m - 3) >> 2) & 1);
      if (m == 3 && warp == 0 && leader) TLREC(5 + wg * 8);
      uint64_t da = da0 + (m & 3) * 1024, db = mkdesc(slotb(sl), 8192, 1024, 1);
      wg_fence();
#pragma unroll
      for (int k = 0; k < 4; k++) wgmma_ss_bf16_n160(acc, da + (k >> 1) * 256 + (k & 1) * 2, db + k * 128, 1);
      wg_commit();
      if (warp == 0 && leader && (m == 3 || m == 6)) { poll_acquire(hcnt + (m == 3 ? 32 : 64), ep * 16); fence_async_all(); }
      __syncwarp();
      wg_wait<1>();
      if (leader) {
        if (warp == 0 && m < 11) load2a(m + 3);
        if (warp == 1 && last_of_two(sb + REL + (9 + m) * 4)) {
          if (m < 12) load2b(m + 2); else mbar_arrive_cluster(mapa(bar(B_PEER), srank ^ 1));
        }
      }
      __syncwarp();
    }
    {
      mbar_wait(bar(B_FULLB + 1), 0);
      mbar_wait(bar(B_FULLA + wg * 4 + 1), 0);
      uint64_t da = da0 + 1024, db = mkdesc(slotb(1), 8192, 1024, 1);
      wg_fence();
      wgmma_ss_bf16_n160(acc, da, db, 1);
      wgmma_ss_bf16_n160(acc, da + 2, db + 128, 1);
      wg_commit();
    }
    const int ooff = (iblk * 128 + wid * 16 + srank * 8 + g) * D + q * 8;
    uint4 xv[5];
#pragma unroll
    for (int u = 0; u < 5; u++) xv[u] = __ldg(reinterpret_cast<const uint4*>(P.x + ooff + (u < 4 ? blk2 * 64 + u * 32 : hb2 * 32)));
    mbar_wait_cl(bar(B_PEER), 0);
    wg_wait<0>();
    reg_pin<80>(acc);
    if (warp == 0 && leader) TLREC(6 + wg * 8);
    {
      const uint32_t ra = mapa(sb + XCH + tid * 16, srank ^ 1), rb = mapa(bar(B_XCH), srank ^ 1);
#pragma unroll
      for (int u = 0; u < 5; u++) {
        const float4 c0 = lds128f(sb + EP2 + u * 128 + q * 16), c1 = lds128f(sb + EP2 + u * 128 + 64 + q * 16);
        const float* a = acc + u * 16;
        asm volatile("st.async.weak.shared::cluster.mbarrier::complete_tx::bytes.v4.b32 [%0], {%1,%2,%3,%4}, [%5];"
                     ::"r"(ra + u * 4096), "r"(pack_bf16(fmaf(0.5f, a[2], c0.x), fmaf(0.5f, a[3], c0.y))), "r"(pack_bf16(fmaf(0.5f, a[6], c0.z), fmaf(0.5f, a[7], c0.w))),
                       "r"(pack_bf16(fmaf(0.5f, a[10], c1.x), fmaf(0.5f, a[11], c1.y))), "r"(pack_bf16(fmaf(0.5f, a[14], c1.z), fmaf(0.5f, a[15], c1.w))), "r"(rb) : "memory");
      }
    }
    const uint32_t ya = sb + YC + lane * 128 + ((wid ^ (lane & 7)) << 4) - cblk * 5 * 4096;
    const uint32_t xw = sb + XCH + wid * 512, ta = xw + (lane & 7) * 64 + (((lane >> 3) ^ ((lane >> 1) & 3)) << 4), tb = xw + g * 64 + ((q ^ (lane >> 3)) << 4);
    mbar_wait(bar(B_YC), 0);
    mbar_wait_cl(bar(B_XCH), 0);
    if (warp == 0 && leader) TLREC(7 + wg * 8);
#pragma unroll
    for (int u = 0; u < 5; u++) {
      uint32_t yv[4], pk[4];
      ldsm4t(ya + (u < 4 ? blk2 * 2 + u : hb2) * 4096, yv[0], yv[1], yv[2], yv[3]);
      const uint4 rv = lds128(xw + u * 4096 + lane * 16);
      const uint32_t r[4] = {rv.x, rv.y, rv.z, rv.w};
#pragma unroll
      for (int e = 0; e < 4; e++) {
        const float h0 = fmaf(0.5f, acc[u * 16 + e * 4], bf_lo(r[e])), h1 = fmaf(0.5f, acc[u * 16 + e * 4 + 1], bf_hi(r[e]));
        pk[e] = bmul2(yv[e], pack_bf16(fmaf(h0, tanh_fast(h0), h0), fmaf(h1, tanh_fast(h1), h1)));
      }
      stsm4(ta + u * 4096, pk[0], pk[1], pk[2], pk[3]);
      __syncwarp();
      const uint4 p = lds128(tb + u * 4096);
      *reinterpret_cast<uint4*>(P.out + ooff + (u < 4 ? blk2 * 64 + u * 32 : hb2 * 32)) =
          make_uint4(badd2(xv[u].x, p.x), badd2(xv[u].y, p.y), badd2(xv[u].z, p.z), badd2(xv[u].w, p.w));
    }
    if (tid == 0) { g_epoch[bid] = ep; TLGT(63); }
    if (warp == 0 && leader) TLREC(8 + wg * 8);
  }
}

typedef CUresult (*EncodeFn)(CUtensorMap*, CUtensorMapDataType, cuuint32_t, void*, const cuuint64_t*, const cuuint64_t*,
                             const cuuint32_t*, const cuuint32_t*, CUtensorMapInterleave, CUtensorMapSwizzle,
                             CUtensorMapL2promotion, CUtensorMapFloatOOBfill);

void make_map(EncodeFn fn, CUtensorMap* tm, const void* base, int cols, int rows, int box_rows) {
  cuuint64_t dims[2] = {(cuuint64_t)cols, (cuuint64_t)rows}, strides[1] = {(cuuint64_t)cols * 2};
  cuuint32_t box[2] = {64, (cuuint32_t)box_rows}, es[2] = {1, 1};
  fn(tm, CU_TENSOR_MAP_DATA_TYPE_BFLOAT16, 2, const_cast<void*>(base), dims, strides, box, es,
     CU_TENSOR_MAP_INTERLEAVE_NONE, CU_TENSOR_MAP_SWIZZLE_128B, CU_TENSOR_MAP_L2_PROMOTION_L2_128B, CU_TENSOR_MAP_FLOAT_OOB_FILL_NONE);
}

}

extern "C" void kernel_launch(void* const* d_in, const int* in_sizes, int n_in, void* d_out, int out_size) {
  static EncodeFn fn = nullptr;
  if (!fn) {
    void* p = nullptr;
    cudaDriverEntryPointQueryResult qr;
    cudaGetDriverEntryPoint("cuTensorMapEncodeTiled", &p, cudaEnableDefault, &qr);
    fn = (EncodeFn)p;
    cudaFuncSetAttribute(fused_kernel, cudaFuncAttributeMaxDynamicSharedMemorySize, SMEM_TOTAL);
  }
  typedef const __nv_bfloat16* bp;
  Params P{(bp)d_in[0], (bp)d_in[1], (bp)d_in[2], (bp)d_in[3], (bp)d_in[4], (bp)d_in[5], (bp)d_in[6],
           (bp)d_in[8], (bp)d_in[9], (bp)d_in[10], (bp)d_in[11], (__nv_bfloat16*)d_out};
  CUtensorMap tx, tw1, tw2;
  make_map(fn, &tx, P.x, D, L, 128);
  make_map(fn, &tw1, P.w1, F, D, 64);
  make_map(fn, &tw2, P.w2, D, F, 64);
  fused_kernel<<<128, 384, SMEM_TOTAL, cudaStreamPerThread>>>(tx, tw1, tw2, P);
}
```

```cpp
#include <cuda_runtime.h>
#include <cuda_bf16.h>
#include <cuda_fp16.h>
#include <cuda.h>
#include <stdint.h>

#define YPRE 0
#define XC0 5
#define XC1 5
#define DL2 1
#define RDW 1
#define PRL 1
#define XVM 14
#define CBM 0
#define XT 0
#define STG 0
#define STY 1
#define PRE 1
#define HX 0
#define NCL 0
#define XNC 2
#define LNC 0
#define XST 1
#define LM 0
#define PDP 2
namespace {

constexpr int L = 2048, D = 640, F = 1728;

__device__ __align__(1024) __half        g_xnT[D * L];
__device__ __align__(1024) __nv_bfloat16 g_h[L * F];
__device__ __align__(1024) __nv_bfloat16 g_yc[D * L];
__device__ __align__(128) uint4 g_stats[L];
__device__ __align__(128) float g_cs[2 * F];
__device__ unsigned       g_cnt[128 * 32];
__device__ unsigned       g_epoch[128];
#define TLM 0xffffffffffffffffull
#define TLX 0
#define TLREC(slot) do {} while (0)
#define TLGT(slot) do {} while (0)
#define DEFER 0
#define DEC 0
#define WRP 1
#define CSP 0
#define TOK 0
#define ROT 256
#define WARM 0
#define FPA 9
#define FPB 3
#define KORD 0
#define PFIRST 1
#define TOK2 1
constexpr int CNT_PREP = 0, CNT_CONV = 1  , CNT_CS = 5, CNT_H = 8  ;

constexpr int WR = 32768, X2 = 131072;
constexpr int AUX = 147456;
constexpr int KA = AUX, KA_C1 = 1984, KA_SZ = 2 * KA_C1, KA_4 = 1120, KA_8 = KA_4 + 448;
constexpr int UU = AUX + 19968, U_SZ = 4352;
constexpr int V5 = UU + 5 * U_SZ, V3 = V5 + 3328, V9 = V3 + 3328, V7 = V9 + 2176;
constexpr int PD = V7 + 2048, PD_H = 2368, P4 = PD + 4 * PD_H, P8 = P4 + 8960, P8_H = 1600;
constexpr int TBG = WR + 4 * 16384, TB_SZ = 7168, LNT = V5, PS = LNT + 20480, PS_SZ = 1280, PT = PS + 12 * PS_SZ;
constexpr int YC = AUX, SPARE = WR + 12288;
constexpr int MISC = AUX + 77696;
constexpr int AT = MISC, BT = AT + 2048, CSS = BT, EP2 = BT + 3584, SCL = EP2 + 640, FLG = SCL + 64, LS2 = SCL + 128, LS1 = SCL + 256, LS3 = SCL + 512, BAR = SCL + 640;
constexpr int XB = FLG + 16;
static_assert(!LM || XC0 == 5, "barriers");
constexpr int SMEM_TOTAL = BAR + 256;
static_assert(P8 + 4 * P8_H <= MISC && PT + 96 <= MISC && TBG + 12 * TB_SZ <= LNT && KA + 5 * KA_SZ <= UU, "overflow");
static_assert(UU % 256 == 0 && U_SZ % 256 == 0 && LNT % 128 == 0 && MISC % 128 == 0 && SMEM_TOTAL <= 232448, "smem");
enum { B_FULL = 0, B_EMPTY = 6, B_HRDY = 12, B_STD = 15, B_EPI1 = 18, B_GATH = 19, B_XRD = 24, B_PEER = 25, B_YC = 26, B_XCH = 27  , B_RDY = 28 };

__device__ __forceinline__ uint32_t smem_u32(const void* p) { return (uint32_t)__cvta_generic_to_shared(p); }
__device__ __forceinline__ void mbar_init(uint32_t b, int c) { asm volatile("mbarrier.init.shared::cta.b64 [%0], %1;" ::"r"(b), "r"(c)); }
__device__ __forceinline__ void mbar_expect(uint32_t b, uint32_t bytes) { asm volatile("mbarrier.arrive.expect_tx.shared::cta.b64 _, [%0], %1;" ::"r"(b), "r"(bytes) : "memory"); }
__device__ __forceinline__ void mbar_arrive(uint32_t b) { asm volatile("mbarrier.arrive.shared::cta.b64 _, [%0];" ::"r"(b) : "memory"); }
__device__ __forceinline__ uint32_t mapa(uint32_t a, uint32_t cta) { uint32_t r; asm volatile("mapa.shared::cluster.u32 %0, %1, %2;" : "=r"(r) : "r"(a), "r"(cta)); return r; }
__device__ __forceinline__ void mbar_arrive_cluster(uint32_t ra) { asm volatile("mbarrier.arrive.shared::cluster.b64 _, [%0];" ::"r"(ra) : "memory"); }
#define MBAR_WAIT(SEM) \
  asm volatile("{\n.reg .pred p;\n.reg .u32 c;\nmov.u32 c, 0;\nW_LOOP:\nmbarrier.try_wait.parity" SEM ".shared::cta.b64 p, [%0], %1;\n@p bra.uni W_DONE;\n" \
               "add.u32 c, c, 1;\nsetp.lt.u32 p, c, 0x40000;\n@p bra.uni W_LOOP;\ntrap;\nW_DONE:\n}" ::"r"(b), "r"(ph) : "memory")
__device__ __forceinline__ void mbar_wait(uint32_t b, uint32_t ph) { MBAR_WAIT(""); }
__device__ __forceinline__ void mbar_wait_cl(uint32_t b, uint32_t ph) { MBAR_WAIT(".acquire.cluster"); }
#define bar_sync(id, n) asm volatile("bar.sync " #id ", " #n ";" ::: "memory")
__device__ __forceinline__ void fence_async_smem() { asm volatile("fence.proxy.async.shared::cta;" ::: "memory"); }
__device__ __forceinline__ void fence_async_all() { asm volatile("fence.proxy.async.global;" ::: "memory"); }
__device__ __forceinline__ void tma2d(uint32_t dst, const CUtensorMap* tm, int c0, int c1, uint32_t bar) {
  asm volatile("cp.async.bulk.tensor.2d.shared::cluster.global.mbarrier::complete_tx::bytes [%0], [%1, {%3, %4}], [%2];"
               ::"r"(dst), "l"(tm), "r"(bar), "r"(c0), "r"(c1) : "memory");
}
__device__ __forceinline__ void tma3d(uint32_t dst, const CUtensorMap* tm, int c1, int c2, uint32_t bar) {
  asm volatile("cp.async.bulk.tensor.3d.shared::cluster.global.mbarrier::complete_tx::bytes [%0], [%1, {%5, %3, %4}], [%2];"
               ::"r"(dst), "l"(tm), "r"(bar), "r"(c1), "r"(c2), "r"(0) : "memory");
}
__device__ __forceinline__ void tma4d(uint32_t dst, const CUtensorMap* tm, int c2, int c3, uint32_t bar) {
  asm volatile("cp.async.bulk.tensor.4d.shared::cluster.global.mbarrier::complete_tx::bytes [%0], [%1, {%5, %5, %3, %4}], [%2];"
               ::"r"(dst), "l"(tm), "r"(bar), "r"(c2), "r"(c3), "r"(0) : "memory");
}
__device__ __forceinline__ void yield_wait(uint32_t a) {
  asm volatile("{\n.reg .pred p;\n.reg .u32 c, v;\nmov.u32 c, 0;\nY_LOOP:\nld.volatile.shared.b32 v, [%0];\nsetp.eq.u32 p, v, 0;\n@p bra.uni Y_DONE;\n"
               "add.u32 c, c, 1;\nsetp.lt.u32 p, c, 0x1000;\n@p bra.uni Y_LOOP;\nY_DONE:\n}" ::"r"(a) : "memory");
}
__device__ __forceinline__ int fresh_lane() { int v; asm volatile("shfl.sync.idx.b32 %0, %1, %1, 31, -1;" : "=r"(v) : "r"(threadIdx.x & 31)); return v; }
#define FRESH const int lane = fresh_lane(), tid = wid * 32 + lane, t = warp * 32 + lane, g = lane >> 2, q = lane & 3; (void)tid; (void)t; (void)g; (void)q;
__device__ __forceinline__ bool elect() {
  uint32_t p;
  asm volatile("{\n.reg .pred p;\nelect.sync _|p, 0xffffffff;\nselp.u32 %0,1,0,p;\n}" : "=r"(p));
  return p;
}
__device__ __forceinline__ void bulk_load(uint32_t dst, const void* src, uint32_t bytes, uint32_t bar) {
  asm volatile("cp.async.bulk.shared::cluster.global.mbarrier::complete_tx::bytes [%0], [%1], %2, [%3];" ::"r"(dst), "l"(src), "r"(bytes), "r"(bar) : "memory");
}
__device__ __forceinline__ void bulk_store(void* dst, uint32_t src, uint32_t bytes) {
  asm volatile("cp.async.bulk.global.shared::cta.bulk_group [%0], [%1], %2;" ::"l"(dst), "r"(src), "r"(bytes) : "memory");
}
__device__ __forceinline__ void bulk_add(void* dst, uint32_t src, uint32_t bytes) {
  asm volatile("cp.reduce.async.bulk.global.shared::cta.bulk_group.add.f32 [%0], [%1], %2;" ::"l"(dst), "r"(src), "r"(bytes) : "memory");
}
__device__ __forceinline__ void bulk_commit() { asm volatile("cp.async.bulk.commit_group;" ::: "memory"); }
template <int N> __device__ __forceinline__ void bulk_wait() { asm volatile("cp.async.bulk.wait_group %0;" ::"n"(N) : "memory"); }
__device__ __forceinline__ void red_release(unsigned* p) { asm volatile("red.release.gpu.global.add.u32 [%0], 1;" ::"l"(p) : "memory"); }
__device__ __forceinline__ void red_relaxed(unsigned* p) { asm volatile("red.relaxed.gpu.global.add.u32 [%0], 1;" ::"l"(p) : "memory"); }
__device__ __forceinline__ uint32_t ldg32(const void* p) { uint32_t v; asm volatile("ld.relaxed.gpu.global.b32 %0, [%1];" : "=r"(v) : "l"(p)); return v; }
__device__ __forceinline__ uint32_t ldg16(const void* p) { unsigned short v; asm volatile("ld.relaxed.gpu.global.b16 %0, [%1];" : "=h"(v) : "l"(p)); return v; }
__device__ __forceinline__ uint4 ldg128(const void* p) { uint4 v; asm volatile("ld.relaxed.gpu.global.v4.b32 {%0,%1,%2,%3}, [%4];" : "=r"(v.x), "=r"(v.y), "=r"(v.z), "=r"(v.w) : "l"(p)); return v; }
#define XLD "ld.global.nc"
__device__ __forceinline__ uint4 ldx128(const void* p) { uint4 v; asm volatile(XLD ".v4.b32 {%0,%1,%2,%3}, [%4];" : "=r"(v.x), "=r"(v.y), "=r"(v.z), "=r"(v.w) : "l"(p)); return v; }
__device__ __forceinline__ float stdev(float var) {
  float s;
  asm("sqrt.approx.f32 %0, %1;" : "=f"(s) : "f"(__bfloat162float(__float2bfloat16_rn(__bfloat162float(__float2bfloat16_rn(var)) + 1e-5f))));
  return __bfloat162float(__float2bfloat16_rn(s));
}
__device__ __forceinline__ float rcp(float x) { float r; asm("rcp.approx.f32 %0, %1;" : "=f"(r) : "f"(x)); return r; }
#define PLD "ld.relaxed"
#define PFN "fence.acquire.gpu;\n"
__device__ __forceinline__ void poll_acquire(const unsigned* p, unsigned target) {
  asm volatile("{\n.reg .pred p;\n.reg .u32 c;\n.reg .s32 v;\nmov.u32 c, 0;\nP_LOOP:\n" PLD ".gpu.global.s32 v, [%0];\nsub.s32 v, v, %1;\nsetp.ge.s32 p, v, 0;\n@p bra P_DONE;\n"
               "add.u32 c, c, 1;\nsetp.lt.u32 p, c, 0x40000;\n@p bra P_LOOP;\ntrap;\nP_DONE:\n" PFN "}" ::"l"(p), "r"(target) : "memory");
}
__device__ __forceinline__ void wg_fence() { asm volatile("wgmma.fence.sync.aligned;" ::: "memory"); }
__device__ __forceinline__ void wg_commit() { asm volatile("wgmma.commit_group.sync.aligned;" ::: "memory"); }
template <int N> __device__ __forceinline__ void wg_wait() { asm volatile("wgmma.wait_group.sync.aligned %0;" ::"n"(N) : "memory"); }
template <int N> __device__ __forceinline__ void reg_pin(float* d) {
#pragma unroll
  for (int i = 0; i < N; i++) asm volatile("" : "+f"(d[i])::"memory");
}
__device__ __forceinline__ uint64_t mkdesc(uint32_t addr, uint32_t lbo, uint32_t sbo, uint32_t swz) {
  return (uint64_t)((addr & 0x3FFFF) >> 4) | ((uint64_t)(lbo >> 4) << 16) | ((uint64_t)(sbo >> 4) << 32) | ((uint64_t)swz << 62);
}
__device__ __forceinline__ float lds16h(uint32_t a) { float v; asm volatile("{\n.reg .b16 h;\nld.shared.b16 h, [%1];\ncvt.f32.f16 %0, h;\n}" : "=f"(v) : "r"(a)); return v; }
__device__ __forceinline__ uint32_t lds32(uint32_t a) { uint32_t v; asm volatile("ld.shared.b32 %0, [%1];" : "=r"(v) : "r"(a)); return v; }
__device__ __forceinline__ float lds32f(uint32_t a) { float v; asm volatile("ld.shared.f32 %0, [%1];" : "=f"(v) : "r"(a)); return v; }
__device__ __forceinline__ uint2 lds64(uint32_t a) { uint2 v; asm volatile("ld.shared.v2.b32 {%0,%1}, [%2];" : "=r"(v.x), "=r"(v.y) : "r"(a)); return v; }
__device__ __forceinline__ uint4 lds128(uint32_t a) { uint4 v; asm volatile("ld.shared.v4.b32 {%0,%1,%2,%3}, [%4];" : "=r"(v.x), "=r"(v.y), "=r"(v.z), "=r"(v.w) : "r"(a)); return v; }
__device__ __forceinline__ float4 lds128f(uint32_t a) { float4 v; asm volatile("ld.shared.v4.f32 {%0,%1,%2,%3}, [%4];" : "=f"(v.x), "=f"(v.y), "=f"(v.z), "=f"(v.w) : "r"(a)); return v; }
__device__ __forceinline__ void sts16(uint32_t a, unsigned short v) { asm volatile("st.shared.b16 [%0], %1;" ::"r"(a), "h"(v) : "memory"); }
__device__ __forceinline__ void sts32(uint32_t a, uint32_t v) { asm volatile("st.shared.b32 [%0], %1;" ::"r"(a), "r"(v) : "memory"); }
__device__ __forceinline__ void sts32f(uint32_t a, float v) { asm volatile("st.shared.f32 [%0], %1;" ::"r"(a), "f"(v) : "memory"); }
__device__ __forceinline__ void sts64(uint32_t a, uint32_t x, uint32_t y) { asm volatile("st.shared.v2.b32 [%0], {%1,%2};" ::"r"(a), "r"(x), "r"(y) : "memory"); }
__device__ __forceinline__ void sts64f(uint32_t a, float x, float y) { asm volatile("st.shared.v2.f32 [%0], {%1,%2};" ::"r"(a), "f"(x), "f"(y) : "memory"); }
__device__ __forceinline__ void sts128(uint32_t a, uint32_t x, uint32_t y, uint32_t z, uint32_t w) { asm volatile("st.shared.v4.b32 [%0], {%1,%2,%3,%4};" ::"r"(a), "r"(x), "r"(y), "r"(z), "r"(w) : "memory"); }
__device__ __forceinline__ void sts128f(uint32_t a, float x, float y, float z, float w) { asm volatile("st.shared.v4.f32 [%0], {%1,%2,%3,%4};" ::"r"(a), "f"(x), "f"(y), "f"(z), "f"(w) : "memory"); }
__device__ __forceinline__ void stsm4(uint32_t a, uint32_t r0, uint32_t r1, uint32_t r2, uint32_t r3) {
  asm volatile("stmatrix.sync.aligned.m8n8.x4.shared.b16 [%0], {%1,%2,%3,%4};" ::"r"(a), "r"(r0), "r"(r1), "r"(r2), "r"(r3) : "memory");
}
__device__ __forceinline__ void stsm4t(uint32_t a, uint32_t r0, uint32_t r1, uint32_t r2, uint32_t r3) {
  asm volatile("stmatrix.sync.aligned.m8n8.x4.trans.shared.b16 [%0], {%1,%2,%3,%4};" ::"r"(a), "r"(r0), "r"(r1), "r"(r2), "r"(r3) : "memory");
}
__device__ __forceinline__ void ldsm4t(uint32_t a, uint32_t& r0, uint32_t& r1, uint32_t& r2, uint32_t& r3) {
  asm volatile("ldmatrix.sync.aligned.m8n8.x4.trans.shared.b16 {%0,%1,%2,%3}, [%4];" : "=r"(r0), "=r"(r1), "=r"(r2), "=r"(r3) : "r"(a) : "memory");
}
__device__ __forceinline__ uint32_t pack_bf16(float lo, float hi) { uint32_t r; asm("cvt.rn.bf16x2.f32 %0, %1, %2;" : "=r"(r) : "f"(hi), "f"(lo)); return r; }
__device__ __forceinline__ uint32_t pack_f16(float lo, float hi) { uint32_t r; asm("cvt.rn.f16x2.f32 %0, %1, %2;" : "=r"(r) : "f"(hi), "f"(lo)); return r; }
__device__ __forceinline__ float bf_lo(uint32_t v) { return __uint_as_float(v << 16); }
__device__ __forceinline__ float bf_hi(uint32_t v) { return __uint_as_float(v & 0xffff0000u); }
__device__ __forceinline__ float bfr(float v) { return __bfloat162float(__float2bfloat16_rn(v)); }
__device__ __forceinline__ float tanh_fast(float x) { float y; asm("tanh.approx.f32 %0, %1;" : "=f"(y) : "f"(x)); return y; }
__device__ __forceinline__ float ex2(float x) { float y; asm("ex2.approx.ftz.f32 %0, %1;" : "=f"(y) : "f"(x)); return y; }
__device__ __forceinline__ uint32_t hadd2u(uint32_t a, uint32_t b) { uint32_t r; asm("add.rn.f16x2 %0, %1, %2;" : "=r"(r) : "r"(a), "r"(b)); return r; }
__device__ __forceinline__ void ldsm2t(uint32_t a, uint32_t& r0, uint32_t& r1) {
  asm volatile("ldmatrix.sync.aligned.m8n8.x2.trans.shared.b16 {%0,%1}, [%2];" : "=r"(r0), "=r"(r1) : "r"(a) : "memory");
}
__device__ __forceinline__ uint32_t hfma2u(uint32_t a, uint32_t b, uint32_t c) { uint32_t r; asm("fma.rn.f16x2 %0, %1, %2, %3;" : "=r"(r) : "r"(a), "r"(b), "r"(c)); return r; }
__device__ __forceinline__ uint32_t badd2(uint32_t a, uint32_t b) { uint32_t r; asm("add.rn.bf16x2 %0, %1, %2;" : "=r"(r) : "r"(a), "r"(b)); return r; }
__device__ __forceinline__ uint32_t bmul2(uint32_t a, uint32_t b) { uint32_t r; asm("mul.rn.bf16x2 %0, %1, %2;" : "=r"(r) : "r"(a), "r"(b)); return r; }
__device__ __forceinline__ uint4 hadd8(uint4 a, uint4 b) { return make_uint4(hadd2u(a.x, b.x), hadd2u(a.y, b.y), hadd2u(a.z, b.z), hadd2u(a.w, b.w)); }
__device__ __forceinline__ float2 cexp_p(float lr, float wi, float p) {
  float m = ex2(lr * p), th = wi * p;
  return make_float2(m * __cosf(th), m * __sinf(th));
}
__device__ __forceinline__ float2 csq(float2 a) { return make_float2(fmaf(a.x, a.x, -a.y * a.y), (a.x + a.x) * a.y); }
__device__ __forceinline__ float2 cmul(float2 a, float2 b) { return make_float2(fmaf(a.x, b.x, -a.y * b.y), fmaf(a.x, b.y, a.y * b.x)); }
template <bool NEG> __device__ __forceinline__ void pmul(uint32_t re, uint32_t im, uint32_t y, uint32_t& ore, uint32_t& oim) {
  __half2 r = *reinterpret_cast<__half2*>(&re), i = *reinterpret_cast<__half2*>(&im), yy = *reinterpret_cast<__half2*>(&y);
  __half2 a = __hfma2(r, __low2half2(yy), __hneg2(__hmul2(i, __high2half2(yy))));
  __half2 b = NEG ? __hfma2(__hneg2(r), __high2half2(yy), __hneg2(__hmul2(i, __low2half2(yy)))) : __hfma2(r, __high2half2(yy), __hmul2(i, __low2half2(yy)));
  ore = *reinterpret_cast<uint32_t*>(&a); oim = *reinterpret_cast<uint32_t*>(&b);
}
struct Pow8 { uint32_t re[4], im[4]; float2 z2, z4, z6, z8; };
__device__ __forceinline__ Pow8 pow8(float2 z1) {
  Pow8 o;
  o.z2 = csq(z1); float2 z3 = cmul(o.z2, z1); o.z4 = csq(o.z2);
  float2 z5 = cmul(o.z4, z1), z7 = cmul(o.z4, z3); o.z6 = csq(z3); o.z8 = csq(o.z4);
  o.re[0] = pack_f16(1.f, z1.x); o.im[0] = pack_f16(0.f, z1.y); o.re[1] = pack_f16(o.z2.x, z3.x); o.im[1] = pack_f16(o.z2.y, z3.y);
  o.re[2] = pack_f16(o.z4.x, z5.x); o.im[2] = pack_f16(o.z4.y, z5.y); o.re[3] = pack_f16(o.z6.x, z7.x); o.im[3] = pack_f16(o.z6.y, z7.y);
  return o;
}
template <bool NEG> __device__ __forceinline__ void put_tile(uint32_t* r, uint32_t* i, const Pow8& p, float2 y) {
  const uint32_t yy = pack_f16(y.x, y.y);
#pragma unroll
  for (int k = 0; k < 4; k++) pmul<NEG>(p.re[k], p.im[k], yy, r[k], i[k]);
}
__device__ __forceinline__ void mma_f16(float* c, uint32_t a0, uint32_t a1, uint32_t a2, uint32_t a3, uint32_t b0, uint32_t b1) {
  asm volatile("mma.sync.aligned.m16n8k16.row.col.f32.f16.f16.f32 {%0,%1,%2,%3}, {%4,%5,%6,%7}, {%8,%9}, {%0,%1,%2,%3};"
               : "+f"(c[0]), "+f"(c[1]), "+f"(c[2]), "+f"(c[3]) : "r"(a0), "r"(a1), "r"(a2), "r"(a3), "r"(b0), "r"(b1));
}
__device__ __forceinline__ void mma_bf16(float* c, uint32_t a0, uint32_t a1, uint32_t a2, uint32_t a3, uint32_t b0, uint32_t b1) {
  asm volatile("mma.sync.aligned.m16n8k16.row.col.f32.bf16.bf16.f32 {%0,%1,%2,%3}, {%4,%5,%6,%7}, {%8,%9}, {%0,%1,%2,%3};"
               : "+f"(c[0]), "+f"(c[1]), "+f"(c[2]), "+f"(c[3]) : "r"(a0), "r"(a1), "r"(a2), "r"(a3), "r"(b0), "r"(b1));
}
__device__ __forceinline__ void mma_bf16k8(float* c, uint32_t a0, uint32_t a1, uint32_t b0) {
  asm volatile("mma.sync.aligned.m16n8k8.row.col.f32.bf16.bf16.f32 {%0,%1,%2,%3}, {%4,%5}, {%6}, {%0,%1,%2,%3};"
               : "+f"(c[0]), "+f"(c[1]), "+f"(c[2]), "+f"(c[3]) : "r"(a0), "r"(a1), "r"(b0));
}
__device__ __forceinline__ uint32_t bfma2(uint32_t a, uint32_t b, uint32_t c) { uint32_t r; asm("fma.rn.bf16x2 %0, %1, %2, %3;" : "=r"(r) : "r"(a), "r"(b), "r"(c)); return r; }
constexpr float GS = 0.7978845608f / 2.421875f;
__device__ __forceinline__ uint32_t gelu2(uint32_t w) {
  uint32_t t = bmul2(w, bfma2(w, w, 0x401b401bu));
  asm volatile("tanh.approx.bf16x2 %0, %0;" : "+r"(t));
  return bfma2(w, t, w);
}
__device__ __forceinline__ uint32_t split2(float v) { return pack_bf16(v, v - bfr(v)); }
#define bar_arrive(id, n) asm volatile("bar.arrive " #id ", " #n ";" ::: "memory")
__device__ __forceinline__ void wgmma_ss_bf16_n128(float* d, uint64_t da, uint64_t db, int sd){
  asm volatile("{\n.reg .pred p;\nsetp.ne.b32 p, %66, 0;\nwgmma.mma_async.sync.aligned.m64n128k16.f32.bf16.bf16 {%0,%1,%2,%3,%4,%5,%6,%7,%8,%9,%10,%11,%12,%13,%14,%15,%16,%17,%18,%19,%20,%21,%22,%23,%24,%25,%26,%27,%28,%29,%30,%31,%32,%33,%34,%35,%36,%37,%38,%39,%40,%41,%42,%43,%44,%45,%46,%47,%48,%49,%50,%51,%52,%53,%54,%55,%56,%57,%58,%59,%60,%61,%62,%63}, %64, %65, p, 1, 1, 0, 1;\n}"
    : "+f"(d[0]),"+f"(d[1]),"+f"(d[2]),"+f"(d[3]),"+f"(d[4]),"+f"(d[5]),"+f"(d[6]),"+f"(d[7]),"+f"(d[8]),"+f"(d[9]),"+f"(d[10]),"+f"(d[11]),"+f"(d[12]),"+f"(d[13]),"+f"(d[14]),"+f"(d[15]),"+f"(d[16]),"+f"(d[17]),"+f"(d[18]),"+f"(d[19]),"+f"(d[20]),"+f"(d[21]),"+f"(d[22]),"+f"(d[23]),"+f"(d[24]),"+f"(d[25]),"+f"(d[26]),"+f"(d[27]),"+f"(d[28]),"+f"(d[29]),"+f"(d[30]),"+f"(d[31]),"+f"(d[32]),"+f"(d[33]),"+f"(d[34]),"+f"(d[35]),"+f"(d[36]),"+f"(d[37]),"+f"(d[38]),"+f"(d[39]),"+f"(d[40]),"+f"(d[41]),"+f"(d[42]),"+f"(d[43]),"+f"(d[44]),"+f"(d[45]),"+f"(d[46]),"+f"(d[47]),"+f"(d[48]),"+f"(d[49]),"+f"(d[50]),"+f"(d[51]),"+f"(d[52]),"+f"(d[53]),"+f"(d[54]),"+f"(d[55]),"+f"(d[56]),"+f"(d[57]),"+f"(d[58]),"+f"(d[59]),"+f"(d[60]),"+f"(d[61]),"+f"(d[62]),"+f"(d[63]) : "l"(da), "l"(db), "r"(sd));
}
__device__ __forceinline__ void wgmma_ss_bf16_n96(float* d, uint64_t da, uint64_t db, int sd){
  asm volatile("{\n.reg .pred p;\nsetp.ne.b32 p, %50, 0;\nwgmma.mma_async.sync.aligned.m64n96k16.f32.bf16.bf16 {%0,%1,%2,%3,%4,%5,%6,%7,%8,%9,%10,%11,%12,%13,%14,%15,%16,%17,%18,%19,%20,%21,%22,%23,%24,%25,%26,%27,%28,%29,%30,%31,%32,%33,%34,%35,%36,%37,%38,%39,%40,%41,%42,%43,%44,%45,%46,%47}, %48, %49, p, 1, 1, 0, 1;\n}"
    : "+f"(d[0]),"+f"(d[1]),"+f"(d[2]),"+f"(d[3]),"+f"(d[4]),"+f"(d[5]),"+f"(d[6]),"+f"(d[7]),"+f"(d[8]),"+f"(d[9]),"+f"(d[10]),"+f"(d[11]),"+f"(d[12]),"+f"(d[13]),"+f"(d[14]),"+f"(d[15]),"+f"(d[16]),"+f"(d[17]),"+f"(d[18]),"+f"(d[19]),"+f"(d[20]),"+f"(d[21]),"+f"(d[22]),"+f"(d[23]),"+f"(d[24]),"+f"(d[25]),"+f"(d[26]),"+f"(d[27]),"+f"(d[28]),"+f"(d[29]),"+f"(d[30]),"+f"(d[31]),"+f"(d[32]),"+f"(d[33]),"+f"(d[34]),"+f"(d[35]),"+f"(d[36]),"+f"(d[37]),"+f"(d[38]),"+f"(d[39]),"+f"(d[40]),"+f"(d[41]),"+f"(d[42]),"+f"(d[43]),"+f"(d[44]),"+f"(d[45]),"+f"(d[46]),"+f"(d[47]) : "l"(da), "l"(db), "r"(sd));
}
__device__ __forceinline__ void wgmma_ss_bf16_n128k(float* d, uint64_t da, uint64_t db, int sd){
  asm volatile("{\n.reg .pred p;\nsetp.ne.b32 p, %66, 0;\nwgmma.mma_async.sync.aligned.m64n128k16.f32.bf16.bf16 {%0,%1,%2,%3,%4,%5,%6,%7,%8,%9,%10,%11,%12,%13,%14,%15,%16,%17,%18,%19,%20,%21,%22,%23,%24,%25,%26,%27,%28,%29,%30,%31,%32,%33,%34,%35,%36,%37,%38,%39,%40,%41,%42,%43,%44,%45,%46,%47,%48,%49,%50,%51,%52,%53,%54,%55,%56,%57,%58,%59,%60,%61,%62,%63}, %64, %65, p, 1, 1, 0, 0;\n}"
    : "+f"(d[0]),"+f"(d[1]),"+f"(d[2]),"+f"(d[3]),"+f"(d[4]),"+f"(d[5]),"+f"(d[6]),"+f"(d[7]),"+f"(d[8]),"+f"(d[9]),"+f"(d[10]),"+f"(d[11]),"+f"(d[12]),"+f"(d[13]),"+f"(d[14]),"+f"(d[15]),"+f"(d[16]),"+f"(d[17]),"+f"(d[18]),"+f"(d[19]),"+f"(d[20]),"+f"(d[21]),"+f"(d[22]),"+f"(d[23]),"+f"(d[24]),"+f"(d[25]),"+f"(d[26]),"+f"(d[27]),"+f"(d[28]),"+f"(d[29]),"+f"(d[30]),"+f"(d[31]),"+f"(d[32]),"+f"(d[33]),"+f"(d[34]),"+f"(d[35]),"+f"(d[36]),"+f"(d[37]),"+f"(d[38]),"+f"(d[39]),"+f"(d[40]),"+f"(d[41]),"+f"(d[42]),"+f"(d[43]),"+f"(d[44]),"+f"(d[45]),"+f"(d[46]),"+f"(d[47]),"+f"(d[48]),"+f"(d[49]),"+f"(d[50]),"+f"(d[51]),"+f"(d[52]),"+f"(d[53]),"+f"(d[54]),"+f"(d[55]),"+f"(d[56]),"+f"(d[57]),"+f"(d[58]),"+f"(d[59]),"+f"(d[60]),"+f"(d[61]),"+f"(d[62]),"+f"(d[63]) : "l"(da), "l"(db), "r"(sd));
}
__device__ __forceinline__ void wgmma_ss_bf16_n96k(float* d, uint64_t da, uint64_t db, int sd){
  asm volatile("{\n.reg .pred p;\nsetp.ne.b32 p, %50, 0;\nwgmma.mma_async.sync.aligned.m64n96k16.f32.bf16.bf16 {%0,%1,%2,%3,%4,%5,%6,%7,%8,%9,%10,%11,%12,%13,%14,%15,%16,%17,%18,%19,%20,%21,%22,%23,%24,%25,%26,%27,%28,%29,%30,%31,%32,%33,%34,%35,%36,%37,%38,%39,%40,%41,%42,%43,%44,%45,%46,%47}, %48, %49, p, 1, 1, 0, 0;\n}"
    : "+f"(d[0]),"+f"(d[1]),"+f"(d[2]),"+f"(d[3]),"+f"(d[4]),"+f"(d[5]),"+f"(d[6]),"+f"(d[7]),"+f"(d[8]),"+f"(d[9]),"+f"(d[10]),"+f"(d[11]),"+f"(d[12]),"+f"(d[13]),"+f"(d[14]),"+f"(d[15]),"+f"(d[16]),"+f"(d[17]),"+f"(d[18]),"+f"(d[19]),"+f"(d[20]),"+f"(d[21]),"+f"(d[22]),"+f"(d[23]),"+f"(d[24]),"+f"(d[25]),"+f"(d[26]),"+f"(d[27]),"+f"(d[28]),"+f"(d[29]),"+f"(d[30]),"+f"(d[31]),"+f"(d[32]),"+f"(d[33]),"+f"(d[34]),"+f"(d[35]),"+f"(d[36]),"+f"(d[37]),"+f"(d[38]),"+f"(d[39]),"+f"(d[40]),"+f"(d[41]),"+f"(d[42]),"+f"(d[43]),"+f"(d[44]),"+f"(d[45]),"+f"(d[46]),"+f"(d[47]) : "l"(da), "l"(db), "r"(sd));
}
__device__ __forceinline__ void wgmma_ss_bf16_n160(float* d, uint64_t da, uint64_t db, int sd){
  asm volatile("{\n.reg .pred p;\nsetp.ne.b32 p, %82, 0;\nwgmma.mma_async.sync.aligned.m64n160k16.f32.bf16.bf16 {%0,%1,%2,%3,%4,%5,%6,%7,%8,%9,%10,%11,%12,%13,%14,%15,%16,%17,%18,%19,%20,%21,%22,%23,%24,%25,%26,%27,%28,%29,%30,%31,%32,%33,%34,%35,%36,%37,%38,%39,%40,%41,%42,%43,%44,%45,%46,%47,%48,%49,%50,%51,%52,%53,%54,%55,%56,%57,%58,%59,%60,%61,%62,%63,%64,%65,%66,%67,%68,%69,%70,%71,%72,%73,%74,%75,%76,%77,%78,%79}, %80, %81, p, 1, 1, 0, 1;\n}"
    : "+f"(d[0]),"+f"(d[1]),"+f"(d[2]),"+f"(d[3]),"+f"(d[4]),"+f"(d[5]),"+f"(d[6]),"+f"(d[7]),"+f"(d[8]),"+f"(d[9]),"+f"(d[10]),"+f"(d[11]),"+f"(d[12]),"+f"(d[13]),"+f"(d[14]),"+f"(d[15]),"+f"(d[16]),"+f"(d[17]),"+f"(d[18]),"+f"(d[19]),"+f"(d[20]),"+f"(d[21]),"+f"(d[22]),"+f"(d[23]),"+f"(d[24]),"+f"(d[25]),"+f"(d[26]),"+f"(d[27]),"+f"(d[28]),"+f"(d[29]),"+f"(d[30]),"+f"(d[31]),"+f"(d[32]),"+f"(d[33]),"+f"(d[34]),"+f"(d[35]),"+f"(d[36]),"+f"(d[37]),"+f"(d[38]),"+f"(d[39]),"+f"(d[40]),"+f"(d[41]),"+f"(d[42]),"+f"(d[43]),"+f"(d[44]),"+f"(d[45]),"+f"(d[46]),"+f"(d[47]),"+f"(d[48]),"+f"(d[49]),"+f"(d[50]),"+f"(d[51]),"+f"(d[52]),"+f"(d[53]),"+f"(d[54]),"+f"(d[55]),"+f"(d[56]),"+f"(d[57]),"+f"(d[58]),"+f"(d[59]),"+f"(d[60]),"+f"(d[61]),"+f"(d[62]),"+f"(d[63]),"+f"(d[64]),"+f"(d[65]),"+f"(d[66]),"+f"(d[67]),"+f"(d[68]),"+f"(d[69]),"+f"(d[70]),"+f"(d[71]),"+f"(d[72]),"+f"(d[73]),"+f"(d[74]),"+f"(d[75]),"+f"(d[76]),"+f"(d[77]),"+f"(d[78]),"+f"(d[79]) : "l"(da), "l"(db), "r"(sd));
}
__device__ __forceinline__ void wgmma_rs_f16_n128(float* d, uint32_t a0, uint32_t a1, uint32_t a2, uint32_t a3, uint64_t db, int sd){
  asm volatile("{\n.reg .pred p;\nsetp.ne.b32 p, %69, 0;\nwgmma.mma_async.sync.aligned.m64n128k16.f32.f16.f16 {%0,%1,%2,%3,%4,%5,%6,%7,%8,%9,%10,%11,%12,%13,%14,%15,%16,%17,%18,%19,%20,%21,%22,%23,%24,%25,%26,%27,%28,%29,%30,%31,%32,%33,%34,%35,%36,%37,%38,%39,%40,%41,%42,%43,%44,%45,%46,%47,%48,%49,%50,%51,%52,%53,%54,%55,%56,%57,%58,%59,%60,%61,%62,%63}, {%64,%65,%66,%67}, %68, p, 1, 1, 0;\n}"
    : "+f"(d[0]),"+f"(d[1]),"+f"(d[2]),"+f"(d[3]),"+f"(d[4]),"+f"(d[5]),"+f"(d[6]),"+f"(d[7]),"+f"(d[8]),"+f"(d[9]),"+f"(d[10]),"+f"(d[11]),"+f"(d[12]),"+f"(d[13]),"+f"(d[14]),"+f"(d[15]),"+f"(d[16]),"+f"(d[17]),"+f"(d[18]),"+f"(d[19]),"+f"(d[20]),"+f"(d[21]),"+f"(d[22]),"+f"(d[23]),"+f"(d[24]),"+f"(d[25]),"+f"(d[26]),"+f"(d[27]),"+f"(d[28]),"+f"(d[29]),"+f"(d[30]),"+f"(d[31]),"+f"(d[32]),"+f"(d[33]),"+f"(d[34]),"+f"(d[35]),"+f"(d[36]),"+f"(d[37]),"+f"(d[38]),"+f"(d[39]),"+f"(d[40]),"+f"(d[41]),"+f"(d[42]),"+f"(d[43]),"+f"(d[44]),"+f"(d[45]),"+f"(d[46]),"+f"(d[47]),"+f"(d[48]),"+f"(d[49]),"+f"(d[50]),"+f"(d[51]),"+f"(d[52]),"+f"(d[53]),"+f"(d[54]),"+f"(d[55]),"+f"(d[56]),"+f"(d[57]),"+f"(d[58]),"+f"(d[59]),"+f"(d[60]),"+f"(d[61]),"+f"(d[62]),"+f"(d[63]) : "r"(a0), "r"(a1), "r"(a2), "r"(a3), "l"(db), "r"(sd));
}
__device__ __forceinline__ void wgmma_rs_f16_n96(float* d, uint32_t a0, uint32_t a1, uint32_t a2, uint32_t a3, uint64_t db, int sd){
  asm volatile("{\n.reg .pred p;\nsetp.ne.b32 p, %53, 0;\nwgmma.mma_async.sync.aligned.m64n96k16.f32.f16.f16 {%0,%1,%2,%3,%4,%5,%6,%7,%8,%9,%10,%11,%12,%13,%14,%15,%16,%17,%18,%19,%20,%21,%22,%23,%24,%25,%26,%27,%28,%29,%30,%31,%32,%33,%34,%35,%36,%37,%38,%39,%40,%41,%42,%43,%44,%45,%46,%47}, {%48,%49,%50,%51}, %52, p, 1, 1, 1;\n}"
    : "+f"(d[0]),"+f"(d[1]),"+f"(d[2]),"+f"(d[3]),"+f"(d[4]),"+f"(d[5]),"+f"(d[6]),"+f"(d[7]),"+f"(d[8]),"+f"(d[9]),"+f"(d[10]),"+f"(d[11]),"+f"(d[12]),"+f"(d[13]),"+f"(d[14]),"+f"(d[15]),"+f"(d[16]),"+f"(d[17]),"+f"(d[18]),"+f"(d[19]),"+f"(d[20]),"+f"(d[21]),"+f"(d[22]),"+f"(d[23]),"+f"(d[24]),"+f"(d[25]),"+f"(d[26]),"+f"(d[27]),"+f"(d[28]),"+f"(d[29]),"+f"(d[30]),"+f"(d[31]),"+f"(d[32]),"+f"(d[33]),"+f"(d[34]),"+f"(d[35]),"+f"(d[36]),"+f"(d[37]),"+f"(d[38]),"+f"(d[39]),"+f"(d[40]),"+f"(d[41]),"+f"(d[42]),"+f"(d[43]),"+f"(d[44]),"+f"(d[45]),"+f"(d[46]),"+f"(d[47]) : "r"(a0), "r"(a1), "r"(a2), "r"(a3), "l"(db), "r"(sd));
}
__device__ __forceinline__ void wgmma_rs_f16_n64(float* d, uint32_t a0, uint32_t a1, uint32_t a2, uint32_t a3, uint64_t db, int sd){
  asm volatile("{\n.reg .pred p;\nsetp.ne.b32 p, %37, 0;\nwgmma.mma_async.sync.aligned.m64n64k16.f32.f16.f16 {%0,%1,%2,%3,%4,%5,%6,%7,%8,%9,%10,%11,%12,%13,%14,%15,%16,%17,%18,%19,%20,%21,%22,%23,%24,%25,%26,%27,%28,%29,%30,%31}, {%32,%33,%34,%35}, %36, p, 1, 1, 1;\n}"
    : "+f"(d[0]),"+f"(d[1]),"+f"(d[2]),"+f"(d[3]),"+f"(d[4]),"+f"(d[5]),"+f"(d[6]),"+f"(d[7]),"+f"(d[8]),"+f"(d[9]),"+f"(d[10]),"+f"(d[11]),"+f"(d[12]),"+f"(d[13]),"+f"(d[14]),"+f"(d[15]),"+f"(d[16]),"+f"(d[17]),"+f"(d[18]),"+f"(d[19]),"+f"(d[20]),"+f"(d[21]),"+f"(d[22]),"+f"(d[23]),"+f"(d[24]),"+f"(d[25]),"+f"(d[26]),"+f"(d[27]),"+f"(d[28]),"+f"(d[29]),"+f"(d[30]),"+f"(d[31]) : "r"(a0), "r"(a1), "r"(a2), "r"(a3), "l"(db), "r"(sd));
}

__device__ __forceinline__ void wgmma_n224(float* d, uint64_t da, uint64_t db, int sd) { wgmma_ss_bf16_n128(d, da, db, sd); wgmma_ss_bf16_n96(d + 64, da, db + 512, sd); }
struct Maps { CUtensorMap x, w1, w1h, w2, w2h, xt, yc, xr; };
struct Params {
  const __nv_bfloat16 *x, *logA, *aimag, *cre, *cim, *logdt, *dskip, *w1, *b1, *w2, *b2;
  __nv_bfloat16* out;
};

template <bool ALL>
__device__ __forceinline__ uint4 windows(const uint2& p, const uint4& c, const uint4& n, uint32_t o4, uint32_t o7, uint32_t o9) {
  const uint32_t w[9] = {p.x, p.y, c.x, c.y, c.z, c.w, n.x, n.y, n.z};
  uint32_t o[8], pe[8], s4[4], v5[4], v3[4];
#pragma unroll
  for (int i = ALL ? 0 : 1; i < 8; i++) { o[i] = __byte_perm(w[i], w[i + 1], 0x5432); pe[i] = hadd2u(w[i], o[i]); }
#pragma unroll
  for (int i = 2; i < 6; i++) { s4[i - 2] = hadd2u(pe[i - 1], pe[i]); v5[i - 2] = hadd2u(s4[i - 2], w[i + 1]); v3[i - 2] = hadd2u(o[i + 1], pe[i + 2]); }
  sts128(o4, v5[0], v5[1], v5[2], v5[3]);
  sts128(o4 + V3 - V5, v3[0], v3[1], v3[2], v3[3]);
  if (ALL) {
    uint32_t v7[4], v9[4];
#pragma unroll
    for (int i = 2; i < 6; i++) { uint32_t s6 = hadd2u(s4[i - 2], pe[i + 1]); v7[i - 2] = hadd2u(s6, o[i - 2]); v9[i - 2] = hadd2u(s6, hadd2u(pe[i - 2], w[i + 2])); }
    sts128(o7, v7[0], v7[1], v7[2], v7[3]);
    sts128(o9, v9[0], v9[1], v9[2], v9[3]);
  }
  return make_uint4(pe[4], pe[5], pe[6], pe[7]);
}
__device__ __forceinline__ uint32_t h2b(uint32_t h, float s) {
  float2 f = __half22float2(*reinterpret_cast<__half2*>(&h));
  return pack_bf16(f.x * s, f.y * s);
}
__device__ __forceinline__ uint32_t b2h(uint32_t b, float s) { return pack_f16(bf_lo(b) * s, bf_hi(b) * s); }

__global__ void __cluster_dims__(2, 1, 1) __launch_bounds__(512, 1)
fused_kernel(const Params P, const __grid_constant__ Maps M) {
  extern __shared__ __align__(1024) uint8_t smem_raw[];
  const uint32_t sb = smem_u32(smem_raw);
  const int wid = __shfl_sync(~0u, ((threadIdx.x + ROT) & 511) >> 5, 0), wg = wid >> 2, warp = wid & 3;
  const int lane = threadIdx.x & 31, tid = wid * 32 + lane, g = lane >> 2, q = lane & 3;
  const int bid = blockIdx.x, srank = bid & 1, cblk = (bid >> 1) & 3, iblk = bid >> 3, jblk = 4 * srank + cblk;
  const int own = (7 * cblk) >> 1, blk1 = 14 * srank + own, hb1 = 12 + 14 * ((jblk - 1) >> 1) + ((jblk - 1) & 1);
  const bool has_half = jblk != 0 && jblk != 7;
  const int blk2 = (5 * cblk + 1) >> 1, hb2 = 5 * cblk + ((cblk & 1) ? 0 : 4);
  auto bar = [&](int i) { return sb + BAR + 8 * i; };
  auto xslot = [&](int s) { return sb + (s >= 4 ? X2 : (s & 2) * 8192); };

  auto init = [&]() {
  if (wid == 12) {
    if (elect()) {
      if (sb & 1023) __trap();
#pragma unroll
      for (int i = 0; i < 32; i++) mbar_init(bar(i), i >= B_EMPTY && i < B_STD ? 8 : i == B_EPI1 ? 3 : 1);
      if (XC0 < 5) for (int i = 0; i < 4; i++) mbar_init(sb + XB + 8 * i, 1);
      asm volatile("fence.mbarrier_init.release.cluster;" ::: "memory");
      mbar_expect(bar(B_XCH), XC0 * 2048); mbar_expect(bar(B_XCH + 4), XC0 * 2048);
      if (XC0 < 5) for (int i = 0; i < 4; i++) { mbar_expect(sb + XB + 8 * i, (i & 1 ? 5 - XC1 : XC1 - XC0) * 2048); }
      TLREC(1);
    }
    __syncwarp();
  }
  };
  uint4 xr[10];
  if (HX & 1) {
    const __nv_bfloat16* px = P.x + (iblk * 128 + jblk * 16 + (warp & 1) * 8 + g) * D + (warp >> 1) * 320 + q * 8;
#pragma unroll
    for (int i = 0; i < 10; i++)
      asm volatile("{\n.reg .pred p;\nsetp.eq.s32 p, %5, 2;\n@p ld.relaxed.gpu.global.v4.b32 {%0,%1,%2,%3}, [%4];\n}"
                   : "=r"(xr[i].x), "=r"(xr[i].y), "=r"(xr[i].z), "=r"(xr[i].w) : "l"(px + i * 32), "r"(wg));
  }
  if (!(HX & 2)) init();
  long long gt0 = 0;
  if (wg == 2) {
    uint32_t pdsk;
    {
      uint4 wr[10];
      const int t = tid & 127;
      const __nv_bfloat16* px = P.x + (iblk * 128 + jblk * 16 + (warp & 1) * 8 + g) * D + (warp >> 1) * 320 + q * 8;
      const __nv_bfloat16* pw = P.w1 + (iblk * 40 + warp * 10) * F + jblk * 216 + min(lane, 26) * 8;
#pragma unroll
      for (int i = 0; i < 10; i++) if (!(HX & 1)) xr[i] = LNC ? ldx128(px + i * 32) : ldg128(px + i * 32);
      sts32(sb + FLG + warp * 4, 0);
      bar_arrive(2, 512);
      asm volatile("barrier.cluster.arrive.relaxed.aligned;" ::: "memory");
      if (LM) {
        if (t == 0) { mbar_init(sb + XB, 4); mbar_init(sb + XB + 8, 4); }
        bar_sync(1, 128);
      }
      {
      FRESH
      const uint32_t ONE = 0x3f803f80u, sel = (q == (g >> 1)) ? ((g & 1) ? 0x3f800000u : 0x00003f80u) : 0u;
      float c0[4] = {0, 0, 0, 0}, c1[4] = {0, 0, 0, 0}, c2[4] = {0, 0, 0, 0}, c3[4] = {0, 0, 0, 0};
      mma_bf16(c0, xr[0].x, xr[0].y, xr[0].z, xr[0].w, ONE, ONE);
      if (WRP == 0) {
#pragma unroll
        for (int r = 0; r < 10; r++) wr[r] = LNC ? ldx128(pw + r * F) : ldg128(pw + r * F);
      }
#pragma unroll
      for (int i = 1; i < 10; i++) mma_bf16((i & 1) ? c1 : c0, xr[i].x, xr[i].y, xr[i].z, xr[i].w, ONE, ONE);
      float s = (c0[0] + c0[2]) + (c1[0] + c1[2]);
      const uint32_t lsa = sb + LS2 + (t & ~3);
      if (t == 0) TLREC(51);
      sts32f(lsa, s);
      if (PDP == 2) pdsk = ldg16(P.dskip + bid * 5 + min(lane, 4));
      if (WRP == 1) {
#pragma unroll
        for (int r = 0; r < 10; r++) wr[r] = LNC ? ldx128(pw + r * F) : ldg128(pw + r * F);
      }
      if (LM & 1) { __syncwarp(); if (lane == 0) mbar_arrive(sb + XB + 0); mbar_wait(sb + XB + 0, 0); } else { bar_sync(1, 128); }
      if (t == 0) TLREC(53);
      s = (s + lds32f(lsa ^ 64)) * (1.f / D);
      const float mean = bfr(s), dl = s - mean;
      if (WRP == 2) {
#pragma unroll
        for (int r = 0; r < 10; r++) wr[r] = ldg128(pw + r * F + (__float_as_uint(s) & (sb >> 25)));
      }
      const uint32_t nm = pack_bf16(-mean, -mean);
#pragma unroll
      for (int i = 0; i < 4; i++) c0[i] = c1[i] = 0.f;
#pragma unroll
      for (int i = 0; i < 10; i++) {
        xr[i] = make_uint4(badd2(xr[i].x, nm), badd2(xr[i].y, nm), badd2(xr[i].z, nm), badd2(xr[i].w, nm));
        mma_bf16k8(c0, xr[i].x, xr[i].y, xr[i].x); mma_bf16k8(c1, xr[i].x, xr[i].y, xr[i].y);
        mma_bf16k8(c2, xr[i].z, xr[i].w, xr[i].z); mma_bf16k8(c3, xr[i].z, xr[i].w, xr[i].w);
      }
      if (sel) sts32f(lsa + LS3 - LS2, (g & 1) ? (c0[1] + c2[1]) + (c1[3] + c3[3]) : (c0[0] + c2[0]) + (c1[2] + c3[2]));
      if (LM & 1) { __syncwarp(); if (lane == 0) mbar_arrive(sb + XB + 8); mbar_wait(sb + XB + 8, 0); } else { bar_sync(1, 128); }
      if (t == 0) TLREC(54);
      const float var = fmaxf((lds32f(lsa + LS3 - LS2) + lds32f((lsa ^ 64) + LS3 - LS2)) * (1.f / D) - dl * dl, 0.f);
      const float sd = stdev(var), rs = rcp(sd);
      auto colsum = [&]() {
#pragma unroll
      for (int i = 0; i < 4; i++) c0[i] = c1[i] = c2[i] = c3[i] = 0.f;
#pragma unroll
      for (int i = 0; i < 10; i += 2) {
        mma_bf16k8(c0, wr[i].x, wr[i].y, sel); mma_bf16k8(c1, wr[i].z, wr[i].w, sel);
        mma_bf16k8(c2, wr[i + 1].x, wr[i + 1].y, sel); mma_bf16k8(c3, wr[i + 1].z, wr[i + 1].w, sel);
      }
      if (lane < 27) {
        sts128f(sb + CSS + warp * 864 + lane * 32, c0[0] + c2[0], c0[1] + c2[1], c0[2] + c2[2], c0[3] + c2[3]);
        sts128f(sb + CSS + warp * 864 + lane * 32 + 16, c1[0] + c3[0], c1[1] + c3[1], c1[2] + c3[2], c1[3] + c3[3]);
      }
      };
      if (CSP == 0) colsum();
      const uint32_t la = sb + LNT + ((warp >> 1) * 320 + (lane & 6) * 4 + (lane >> 3) * 2 + (lane & 1)) * 32 + (warp & 1) * 16;
#pragma unroll
      for (int i = 0; i < 10; i++) stsm4t(la + i * 1024, b2h(xr[i].x, rs), b2h(xr[i].y, rs), b2h(xr[i].z, rs), b2h(xr[i].w, rs));
      {
        const float s2 = stdev(var * rs * rs);
        const uint32_t m = split2(-0.5f * fmaf(bfr(dl * rs), sd, mean)), v = split2(0.5f * sd * s2), a = split2(GS * rs * rcp(s2));
        if (warp < 2) sts128(sb + LS1 + warp * 128 + g * 16, __byte_perm(m, m, 0x1010), __byte_perm(m, v, 0x5432), __byte_perm(v, a, 0x5432), a >> 16);
      }
      if (CSP == 1) colsum();
      if (t == 0) TLREC(56);
      fence_async_smem();
      bar_arrive(4, 192);
      if (t == 0) TLREC(43);
      if (t == 0) TLREC(44);
      if (PDP == 0) pdsk = ldg16(P.dskip + bid * 5 + min(lane, 4));
      }
    }
    FRESH
    bar_sync(3, 512);
    if (PDP == 1) pdsk = ldg16(P.dskip + bid * 5 + min(lane, 4));
    asm volatile("setmaxnreg.inc.sync.aligned.u32 144;");
    if (t == 0) TLREC(58);
    {
      uint2 pa[12], tl[12];
      float pb[12], dd[5];
#pragma unroll
      for (int i = 0; i < 12; i++) { const uint32_t ps = sb + PS + i * PS_SZ; pa[i] = lds64(ps + t * 8); pb[i] = lds16h(ps + 1024 + t * 2); tl[i] = lds64(sb + PT + i * 8); }
#pragma unroll
      for (int i = 0; i < 5; i++) dd[i] = bf_lo(__shfl_sync(~0u, pdsk, i));
#pragma unroll
      for (int i = 0; i < 9; i++) sts128(sb + KA + t * 16 + i * 2048, 0, 0, 0, 0);
      if (t < 5 * KA_SZ / 16 - 9 * 128) sts128(sb + KA + t * 16 + 9 * 2048, 0, 0, 0, 0);
      if (t < 80) sts128(sb + UU + (t >> 4) * U_SZ + (t & 15) * 16, 0, 0, 0, 0);
      if (t == 0) TLREC(17);
      const int a = t >> 3, c = t & 7;
      const int y2 = (543 - 256 - 128 * (c & 1) - (c & 6) - 8 * a) * 2;
      const int y3 = 95 - ((16 * (c & 3) + a - 1 + (c >> 2)) & 63), y4 = 63 - ((8 * c + (a >> 1) - 1 + (a & 1)) & 63);
      const int o3 = KA_4 + (c >> 2) * 4, o4 = KA_8 + (a & 1) * 4;
      uint32_t h01[5], h2[5], h34[5], ee[5];
#pragma unroll
      for (int ch = 0; ch < 5; ch++) {
        float v[6] = {0, 0, 0, 0, 0, 0}, mx = 0.f;
#pragma unroll
        for (int i = 2 * ch; i < (ch == 4 ? 12 : 2 * ch + 2); i++) {
          const float us = __uint_as_float(tl[i].y);
          const float2 p0 = __half22float2(*reinterpret_cast<__half2*>(&pa[i].x)), p1 = __half22float2(*reinterpret_cast<__half2*>(&pa[i].y));
          v[0] = fmaf(p0.x, us, v[0]); v[1] = fmaf(p0.y, us, v[1]); v[2] = fmaf(p1.x, us, v[2]); v[3] = fmaf(p1.y, us, v[3]);
          v[4] = fmaf(pb[i], us, v[4]); v[5] = fmaf(__uint_as_float(tl[i].x), us, v[5]);
          mx = fmaxf(mx, us);
        }
        const unsigned e = min(__float_as_uint(fmaxf(mx, fabsf(dd[ch]) * (1.f / 64))) >> 23, 240u);
        const float inv = __uint_as_float((246u - e) << 23);
        ee[ch] = (e + 8u) << 23;
        h01[ch] = pack_f16((t ? v[0] : v[0] + dd[ch]) * inv, v[1] * inv); h2[ch] = pack_f16(v[2] * inv, v[3] * inv);
        h34[ch] = pack_f16((t ? v[3] : v[4]) * inv, (t ? v[4] : v[5]) * inv);
      }
      bar_sync(1, 128);
      if (t == 0) TLREC(18);
#pragma unroll
      for (int ch = 0; ch < 5; ch++) {
        const uint32_t k0 = sb + KA + ch * KA_SZ;
        auto put = [&](int yb, unsigned short h) { sts16(k0 + yb, h); sts16(k0 + KA_C1 - 2 + yb, h); };
        auto putf = [&](int o, int y, unsigned short h) {
          sts16(k0 + o + (y >> 1) * 8 + (y & 1) * 2, h); sts16(k0 + KA_C1 + o + ((y - 1) >> 1) * 8 + ((y - 1) & 1) * 2, h);
        };
        put((543 - t) * 2, h01[ch]); put((415 - t) * 2, h01[ch] >> 16); put(y2, h2[ch]);
        if (!(c & 2)) { put(y2 - 2, h2[ch]); put(t ? y2 + 2 : y2, h2[ch]); }
        putf(o3, y3, h34[ch]); putf(o4, y4, h34[ch] >> 16);
      }
      if (t == 0) {
#pragma unroll
        for (int ch = 0; ch < 5; ch++) {
          const uint32_t k0 = sb + KA + ch * KA_SZ, h = __byte_perm(h2[ch], 0, 0x3232);
          sts16(k0 + 58, h); sts32(k0 + 60, h); sts16(k0 + 64, h); sts64(k0 + KA_C1 + 56, h, h);
          sts64(sb + SCL + ch * 8, ee[ch], __byte_perm(h34[ch], 0, 0x1010));
        }
      }
    }
    if (t == 0) TLREC(20);
    mbar_wait(bar(B_XRD), 0);
    bar_sync(1, 128);
    if (t < 33) sts128(sb + (t < 32 ? V5 + (t & 16) * 208 + (t & 15) * 16 : V9 + 1024), 0, 0, 0, 0);
    sts128(sb + (t < 64 ? P4 + t * 16 : P8 + (t >> 5) * P8_H + (t & 31) * 16), 0, 0, 0, 0);
    sts128(sb + P4 + 4096 + t * 16, 0, 0, 0, 0);
    if (t < 64) sts128(sb + PD + (2 + (t >> 5)) * PD_H + (t & 31) * 16, 0, 0, 0, 0);
    {
      float aD[64];
#pragma unroll
      for (int i = 0; i < 64; i++) aD[i] = 0.f;
      const uint32_t hi = warp >> 1;
      const uint32_t kcp = (g & 1) ? 0 : KA_C1, kw = q - (warp & 1) * 4, flg = sb + FLG + warp * 4;
      uint32_t kk = (kcp + 4 * (((415 - g) >> 1) - 136 * hi + kw)) | t << 12 | (kcp + KA_4 + 8 * (((63 - g) >> 1) - 24 * hi + kw)) << 20;
      uint32_t ka = sb + KA;
      auto chunk = [](int c) { return (c * 16) ^ ((c & 8) * 2); };
      uint32_t uu = sb + UU;
      auto tidx = [&](int z) { return ((kk + (uu >> z)) >> 12) & 127; };
      uint4 y0, y1, y2, y3;
      uint32_t rd, r4;
      auto finish0 = [&]() {
        const uint32_t tv = tidx(25);
        rd = sb + PD + (tv & 1) * PD_H + (tv >> 1) * 16; r4 = sb + P4 + tv * 16;
        y0 = lds128(rd + 272); y1 = lds128(rd + 2 * PD_H); y2 = lds128(r4); y3 = lds128(r4 + 4096);
      };
      auto finish = [&](int ch) {
        const uint2 sc = lds64(sb + SCL - 8 + ch * 8);
        const float os = __uint_as_float(sc.x);
        uint4 y = hadd8(hadd8(y0, y1), hadd8(y2, y3));
        y0 = lds128(rd + 272 + 1024); y1 = lds128(rd + 2 * PD_H + 1024); y2 = lds128(r4 + 2048); y3 = lds128(r4 + 4096 + 2048);
        y = make_uint4(h2b(y.x, os), h2b(y.y, os), h2b(y.z, os), h2b(y.w, os));
        const uint32_t tv = tidx(26), r8 = rd + P8 - PD + (tv & 1) * (P8_H - PD_H), yo = uu + 256 - U_SZ + (tv >> 4) * 256 + (tv & 1) * 128 + (tv & 14) * 8;
        uint4 z0 = lds128(r8 + 512), z = lds128(r8 + 2 * P8_H);
        const uint4 p2 = lds128(ka - KA_SZ + tv * 16);
        sts128(yo, y.x, y.y, y.z, y.w);
        y = hadd8(hadd8(y0, y1), hadd8(y2, y3));
        z = hadd8(z, z0);
        y = hadd8(y, make_uint4(hfma2u(p2.x, sc.y, z.x), hfma2u(p2.y, sc.y, z.y), hfma2u(p2.z, sc.y, z.z), hfma2u(p2.w, sc.y, z.w)));
        sts128(yo + 2048, h2b(y.x, os), h2b(y.y, os), h2b(y.z, os), h2b(y.w, os));
        fence_async_smem();
        if (((TLM >> 24) & 31) && tv == 0) TLREC(23 + ch);
      };
#pragma unroll 1
      for (int ch = 0;; ch++) {
        uint4 p2n;
        if (ch < 5) {
          mbar_wait(bar(B_GATH + ch), 0);
          if (((TLM >> 23) & 1) && tidx(27) == 0 && ch == 0) TLREC(23);
          const uint32_t tv = tidx(27), un = uu + 256 + chunk(tv), uc = uu + chunk(tv + 15), up = uu + chunk(tv + 14) + 8;
          const uint2 p = lds64(up);
          const uint4 c = lds128(uc), n = lds128(un);
          const uint2 p1 = make_uint2(0, lds32(up + 2052));
          const uint4 c1 = lds128(uc + 2048), n1 = lds128(un + 2048);
          p2n = windows<true>(p, c, n, sb + V5 + 256 + tv * 16, sb + V7 + (~tv & 1) * 1024 + (tv >> 1) * 16, sb + V9 + (tv & 1) * 1024 + ((tv + 1) >> 1) * 16);
          if (warp < 2) windows<false>(p1, c1, n1, sb + V5 + 256 + 2048 + tv * 16, 0, 0);
          fence_async_smem();
        }
        wg_wait<0>();
        reg_pin<64>(aD);
        uint2 f4[10];
        const uint32_t kf = ka + ((kk + (uu >> 30)) >> 20);
#pragma unroll
        for (int i = 0; i < 10; i++) f4[i] = lds64(i < 6 ? kf + 32 * i : kf + hi * 64 + 384 + 32 * (i - 6));
        if (FPA == 0 && ch < 5) sts32(flg, 1);
        {
          uint32_t pk[16];
          pk[0] = pack_f16(aD[0], aD[1]);
#pragma unroll
          for (int j = 1; j < 16; j++) pk[j] = pack_f16(aD[4 * j] + aD[4 * j - 2], aD[4 * j + 1] + aD[4 * j - 1]);
          const uint32_t pa = sb + PD + warp * (PD_H - 512) + 272 + tidx(28) * 16;
#pragma unroll
          for (int j = 0; j < 16; j += 4) stsm4t(pa + j * 128, pk[j], pk[j + 1], pk[j + 2], pk[j + 3]);
        }
        if (FPA == 1 && ch < 5) sts32(flg, 1);
        bar_sync(1, 128);
        finish0();
        if (ch == 5) break;
        if (FPA == 2) sts32(flg, 1);
        float a4[48], a8[32];
        {
          const uint64_t d4 = mkdesc(sb + V5, V3 - V5, 256, 0), d8 = mkdesc(sb + V9, V7 - V9, 256, 0);
          wg_fence();
#pragma unroll
          for (int m = 0; m < 4; m++) wgmma_rs_f16_n96(a4, m > 1 ? f4[m + 2].x : 0u, f4[m].x, m > 1 ? f4[m + 2].y : 0u, f4[m].y, d4 + m * 8, m);
#pragma unroll
          for (int m = 0; m < 2; m++) wgmma_rs_f16_n64(a8, f4[m + 8].x, f4[m + 6].x, f4[m + 8].y, f4[m + 6].y, d8 + m * 8, m);
          wg_commit();
          sts32(flg, 0);
        }
        if (ch) finish(ch);
        wg_wait<0>();
        reg_pin<48>(a4); reg_pin<32>(a8);
        if (FPB == 0) sts32(flg, 1);
        uint32_t f[34];
        const uint32_t kd = ka + ((kk + (uu >> 31)) & 4095);
#pragma unroll
        for (int i = 0; i < 34; i++) f[i] = lds32(kd - 256 + 16 * i);
        bar_sync(1, 128);
        const uint32_t tv = tidx(29), srow = ((tv & 24) * 2 + (warp & 1) * 8 + (tv & 7)) * 16;
        sts128(ka + tv * 16, p2n.x, p2n.y, p2n.z, p2n.w);
        if (FPB == 1) sts32(flg, 1);
        if (ch && tv == 0) { bulk_store(g_yc + (bid * 5 + ch - 1) * L, uu + 256 - U_SZ, 4096); bulk_commit(); }
        {
          uint32_t pk[12];
          pk[0] = pack_f16(a4[0], a4[1]);
#pragma unroll
          for (int j = 1; j < 12; j++) pk[j] = pack_f16(a4[4 * j] + a4[4 * j - 2], a4[4 * j + 1] + a4[4 * j - 1]);
          const uint32_t pa = sb + P4 + 1024 + hi * 4864 + srow;
#pragma unroll
          for (int j = 0; j < 12; j += 4) stsm4(pa + j * 256, pk[j], pk[j + 1], pk[j + 2], pk[j + 3]);
          if (FPB == 2) sts32(flg, 1);
#pragma unroll
          for (int h = 0; h < 2; h++) {
            pk[0] = pack_f16(a8[16 * h], a8[16 * h + 1]);
#pragma unroll
            for (int j = 1; j < 4; j++) pk[j] = pack_f16(a8[16 * h + 4 * j] + a8[16 * h + 4 * j - 2], a8[16 * h + 4 * j + 1] + a8[16 * h + 4 * j - 1]);
            stsm4(sb + P8 + 512 + (2 * hi + 1 - h) * P8_H + srow, pk[0], pk[1], pk[2], pk[3]);
          }
        }
        {
          const uint64_t du = mkdesc(uu, 16, 256, 3);
          if (FPB == 3) sts32(flg, 1);
          wg_fence();
#pragma unroll
          for (int m = 0; m < 9; m++) wgmma_rs_f16_n128(aD, m ? f[16 + 2 * m] : 0u, f[2 * m], m ? f[17 + 2 * m] : 0u, f[2 * m + 1], du + 2 * m, m);
          wg_commit();
          sts32(flg, 0);
        }
        ka += KA_SZ; uu += U_SZ;
      }
      finish(5);
      bar_sync(1, 128);
      asm volatile("barrier.cluster.wait.acquire.aligned;" ::: "memory");
      if (tidx(25) == 0) {
        const unsigned ep = ldg32(g_epoch + bid) + 1;
        bulk_store(g_yc + (bid * 5 + 4) * L, uu + 256 - U_SZ, 4096);
        bulk_commit();
        bulk_wait<0>();
        red_relaxed(&g_cnt[(CNT_CONV + (bid >> 5)) * 32]);
        TLREC(30);
        if (!XT) mbar_expect(bar(B_YC), 20480);
        if (XT) {
          mbar_expect(bar(B_YC), 40960);
#pragma unroll
          for (int u = 0; u < 5; u++)
            asm volatile("cp.async.bulk.tensor.3d.shared::cluster.global.mbarrier::complete_tx::bytes [%0], [%1, {%2, %3, %4}], [%5];"
                         ::"r"(sb + V5 + u * 4096), "l"(&M.xr), "r"(u < 4 ? blk2 * 64 + u * 32 : hb2 * 32), "r"(srank * 8), "r"(iblk * 8), "r"(bar(B_YC)) : "memory");
        }
        poll_acquire(&g_cnt[(CNT_CONV + cblk) * 32], ep * 32);
        fence_async_all();
        TLREC(31);
        tma2d(sb + YC, &M.yc, iblk * 128 + srank * 64, cblk * 160, bar(B_YC));
      }
    }
  } else {
    auto load1 = [&](int J, int s) {
      const uint32_t fb = bar(B_FULL + s), dst = sb + WR + s * 16384;
      mbar_expect(fb, (has_half ? 14336 : 12288) + ((J & 1) ? 0 : 16384));
      if (J & 1) tma2d(xslot(s), &M.x, J * 32 - 32, iblk * 128, fb - 8);
      tma3d(dst, &M.w1, J * 32, blk1, fb);
      if (has_half) tma2d(dst + 12288, &M.w1h, hb1 * 32, J * 32, fb);
    };
    const int kch = bid * 5 + (wg == 3 ? 4 : wid >> 1), pidx = kch * 64 + ((wg == 3 ? wid >> 1 : wid) & 1) * 32 + lane;
    uint32_t pA = ldg32(P.logA + 2 * pidx), pI = ldg32(P.aimag + 2 * pidx), pR = ldg32(P.cre + 2 * pidx), pC = ldg32(P.cim + 2 * pidx);
    const uint32_t pdt = ldg16(P.logdt + kch);
    if (HX & 2) init();
    if (wg == 3 && elect()) {
      asm volatile("prefetch.tensormap [%0];" ::"l"(&M.x + warp) : "memory");
      asm volatile("prefetch.tensormap [%0];" ::"l"(&M.w2h + warp) : "memory");
    }
    __syncwarp();
    asm volatile("barrier.cluster.arrive.relaxed.aligned;" ::: "memory");
    {
      FRESH
      const int kw = wg == 3 ? wid - 4 : wid;
      const uint32_t tb = sb + TBG + kw * TB_SZ, tw = tb + lane * 16, tr = tb + (lane >> 3) * 512 + (lane & 7) * 16;
      float acc[5][4], fl = 0.f, sc = 0.f, dt = 0.f;
      uint32_t cA = 0, cI = 0, cR = 0, cC = 0;
      unsigned e = 0;
#pragma unroll
      for (int i = 0; i < 5; i++) acc[i][0] = acc[i][1] = acc[i][2] = acc[i][3] = 0.f;
#pragma unroll 1
      for (int rd = WARM ? (wg + 1) / 2 - 1 : wg >> 1; rd < 2; rd++) {
        if (rd >= 0) {
          if (!e) {
            const uint32_t ca = pR & 0x7fff7fffu, cb = pC & 0x7fff7fffu;
            e = __reduce_max_sync(~0u, max(max(ca, cb), max(ca << 16, cb << 16))) >> 23;
            e = min(max(e, 1u), 252u);
            sc = __uint_as_float((253u - e) << 23); dt = bfr(expf(bf_lo(pdt)));
            if (wid >= 8 && (wid & 1)) { pA >>= 16; pI >>= 16; pR >>= 16; pC >>= 16; }
            if (tid == 0) TLREC(40);
            if (lane == 0) TLREC(304 + wid);
            if (wid == 12 && elect()) {
#pragma unroll 1
              for (int J = e >> 8; J < 4; J++) load1(J, J);
            }
            __syncwarp();
          }
          cA = pA; cI = pI; cR = pR; cC = pC;
          pA >>= 16; pI >>= 16; pR >>= 16; pC >>= 16;
        }
        const float lr = -bfr(expf(bf_lo(cA))) * dt * 1.4426950408889634f, wi = bf_lo(cI) * dt;
        const float2 C = make_float2(bf_lo(cR) * sc, bf_lo(cC) * sc);
        const float2 Z = cexp_p(lr, wi, 128.f);
        const Pow8 s = pow8(cexp_p(lr, wi, 1.f));
        uint32_t tt[14][4];
#pragma unroll
        for (int k = 0; k < 4; k++) { tt[4][k] = s.re[k]; tt[5][k] = s.im[k]; }
        put_tile<false>(tt[6], tt[7], s, Z);
        const Pow8 a = pow8(s.z8);
        put_tile<true>(tt[0], tt[2], a, C);
        put_tile<true>(tt[1], tt[3], a, cmul(C, a.z8));
        const Pow8 w = pow8(Z);
        put_tile<false>(tt[12], tt[13], w, w.z8);
        const uint32_t y2 = pack_f16(s.z2.x, s.z2.y), y4 = pack_f16(s.z4.x, s.z4.y), y6 = pack_f16(s.z6.x, s.z6.y);
        tt[8][0] = w.re[1]; tt[9][0] = w.im[1];
        pmul<false>(w.re[1], w.im[1], y2, tt[8][1], tt[9][1]); pmul<false>(w.re[1], w.im[1], y4, tt[8][2], tt[9][2]); pmul<false>(w.re[1], w.im[1], y6, tt[8][3], tt[9][3]);
        tt[10][0] = w.re[2]; tt[10][1] = w.re[3]; tt[11][0] = w.im[2]; tt[11][1] = w.im[3];
        pmul<false>(w.re[2], w.im[2], y4, tt[10][2], tt[11][2]); pmul<false>(w.re[3], w.im[3], y4, tt[10][3], tt[11][3]);
        const float2 zl = csq(w.z8);
        fl += fmaf(C.x, zl.x, -C.y * zl.y);
        const uint32_t ta = tw + ((tt[1][3] ^ tt[3][3] ^ tt[12][3] ^ tt[13][3] ^ (DEFER > 1 ? tt[11][3] ^ tt[9][3] ^ tt[7][3] : 0)) & (DEFER ? tw >> 25 : 0));
#pragma unroll
        for (int k = 0; k < 14; k++) sts128(ta + k * 512, tt[k][0], tt[k][1], tt[k][2], tt[k][3]);
        __syncwarp();
        if (lane == 0 && rd >= 0) TLREC(320 + rd * 32 + wid);
#pragma unroll
        for (int j = 0; j < 4; j++) {
          uint32_t a0, a1, a2, a3, b[10];
          ldsm4t(tr + j * 128, a0, a1, a2, a3);
          ldsm4t(tr + j * 128 + 2048, b[0], b[1], b[2], b[3]);
          ldsm4t(tr + j * 128 + 4096, b[4], b[5], b[6], b[7]);
          ldsm2t(tr + j * 128 + 6144, b[8], b[9]);
#pragma unroll
          for (int k = 0; k < 5; k++) mma_f16(acc[k], a0, a1, a2, a3, b[2 * k], b[2 * k + 1]);
        }
        __syncwarp();
        if (lane == 0 && rd >= 0) TLREC(336 + rd * 32 + wid);
      }
      const uint32_t ps = sb + PS + kw * PS_SZ;
#pragma unroll
      for (int i = 0; i < 2; i++) {
        float r[4] = {0, 0, 0, 0};
        const uint32_t h = pack_f16(fl, fl - __half2float(__float2half_rn(fl))), ONE = 0x3c003c00u;
        if (i) mma_f16(r, h, 0, 0, 0, ONE, 0); else mma_f16(r, ONE, 0, 0, 0, h, 0);
        fl = i ? r[0] : r[0] + r[1];
      }
#pragma unroll
      for (int i = 0; i < 4; i += 2) {
        sts128(ps + i * 256 + lane * 16, pack_f16(acc[0][i], acc[1][i]), pack_f16(acc[2][i], acc[3][i]), pack_f16(acc[0][i + 1], acc[1][i + 1]), pack_f16(acc[2][i + 1], acc[3][i + 1]));
        sts32(ps + 1024 + i * 64 + lane * 4, pack_f16(acc[4][i], acc[4][i + 1]));
      }
      sts64f(sb + PT + kw * 8, fl, 2.f * dt * __uint_as_float((e + 1u) << 23));
      if (tid == 0) TLREC(41);
      if (tid == 384) TLREC(42);
      bar_arrive(3, 512);
    }
    const bool leader = elect();
    if (wg == 3) {
      asm volatile("setmaxnreg.dec.sync.aligned.u32 32;");
      bar_sync(5, 128);
      auto kblock = [&](int J) {
        const int m = (J - 20) >> 1, j = (m * 43) >> 7, p = m - 3 * j, k = m < 3 ? own + m : m < 12 ? ((7 * (KORD ? p + (p >= cblk) : (cblk + p + 1) & 3)) >> 1) + j - 1 : 6;
        return m == 13 ? 26 + srank : 28 * srank + 2 * k + (J & 1);
      };
      if (warp == 0) {
        bar_sync(2, 512);
        asm volatile("barrier.cluster.wait.acquire.aligned;" ::: "memory");
        if (leader) {
          fence_async_smem();
          int s = 4, ph = 1;
#pragma unroll 1
          for (int J = 4; J < 47; J++) {
            mbar_wait(bar(B_EMPTY + s), ph);
            TLREC(64 + J);
            if (J < 20) load1(J, s);
            else {
              const int kb = kblock(J);
              const uint32_t fb = bar(B_FULL + s), dst = sb + WR + s * 16384;
              mbar_expect(fb, J < 26 ? 10240 : 18432);
              tma3d(dst, &M.w2, kb * 32, blk2, fb);
              tma2d(dst + 8192, &M.w2h, hb2 * 32, kb * 32, fb);
            }
            TLREC(128 + J);
            if (++s == 6) { s = 0; ph ^= 1; }
          }
        }
      } else {
        bar_arrive(2, 512);
        const unsigned ep = ldg32(g_epoch + bid) + 1;
        float* cs = g_cs + (ep & 1) * F;
        if (warp == 3) {
          bar_sync(4, 192);
          if (leader) {
            bulk_store(g_xnT + (iblk * 8 + jblk) * 10240, sb + LNT, 20480);
            bulk_store(g_stats + iblk * 128 + jblk * 16, sb + LS1, 256);
            bulk_commit();
            bulk_wait<0>();
            red_relaxed(&g_cnt[CNT_PREP * 32]);
            mbar_arrive(bar(B_XRD));
            TLREC(46);
          }
          __syncwarp();
          bar_sync(6, 288);
          if (leader) {
            fence_async_smem();
            poll_acquire(&g_cnt[CNT_PREP * 32], ep * 128);
            fence_async_all();
            TLREC(22);
#pragma unroll 1
            for (int c = 0; c < 5; c++) {
              mbar_expect(bar(B_GATH + c), 4096);
              tma2d(sb + UU + 256 + c * U_SZ, &M.xt, (bid * 5 + c) * 16, 0, bar(B_GATH + c));
            }
            mbar_expect(bar(B_EPI1), 2048);
            bulk_load(sb + AT, g_stats + iblk * 128, 2048, bar(B_EPI1));
            TLREC(21);
          }
          __syncwarp();
        } else if (warp == 2) {
          uint32_t pb[4];
#pragma unroll
          for (int i = 0; i < 4; i++) pb[i] = ldg32(P.b1 + (i < 3 ? (blk1 + i) * 64 + 2 * lane : (has_half ? hb1 : 0) * 32 + (2 * lane & 31)));
          bar_sync(4, 192);
#pragma unroll
          for (int i = 0; i < 2; i++) {
            const uint32_t ca = sb + CSS + min(lane, 26) * 32 + i * 16;
            float4 a = lds128f(ca), b = lds128f(ca + 864), c = lds128f(ca + 1728), d = lds128f(ca + 2592);
            __syncwarp();
            sts128f(ca, (a.x + b.x) + (c.x + d.x), (a.y + b.y) + (c.y + d.y), (a.z + b.z) + (c.z + d.z), (a.w + b.w) + (c.w + d.w));
          }
          fence_async_smem();
          __syncwarp();
          if (leader) {
            bulk_add(cs + jblk * 216, sb + CSS, 864);
            bulk_commit();
            bulk_wait<0>();
            red_relaxed(&g_cnt[CNT_CS * 32]);
            poll_acquire(&g_cnt[CNT_CS * 32], ep * 128);
          }
          __syncwarp();
          float2 cv[4];
#pragma unroll
          for (int i = 0; i < 4; i++) cv[i] = __ldcg(reinterpret_cast<const float2*>(cs + (i < 3 ? (blk1 + i) * 64 + 2 * lane : (has_half ? hb1 : 0) * 32 + (2 * lane & 31))));
#pragma unroll
          for (int i = 0; i < 4; i++) {
            const uint32_t c0 = split2(cv[i].x), c1 = split2(cv[i].y), a = sb + BT + i * 1024 + (i < 3 ? lane : lane & 15) * 32;
            sts128(a, c0, __byte_perm(c0, pb[i], 0x5410), pb[i] & 0xffffu, 0);
            sts128(a + 16, c1, __byte_perm(c1, pb[i], 0x7610), pb[i] >> 16, 0);
          }
          if (leader) TLREC(29);
          fence_async_smem();
          __syncwarp();
          if (leader) { mbar_arrive(bar(B_EPI1)); TLREC(47); }
        } else {
          if (leader) asm volatile("cp.async.bulk.prefetch.L2.global [%0], %1;" ::"l"(P.w2 + bid * 8640), "r"(17280) : "memory");
#pragma unroll
          for (int i = 0; i < 3; i++) {
            const int t = i < 2 ? lane + 32 * i : 64 + (lane & 15);
            const uint32_t pb = ldg32(P.b2 + (i < 2 ? blk2 * 64 + 2 * t : hb2 * 32 + (2 * t & 31)));
            sts64f(sb + EP2 + (t >> 3) * 64 + (t & 3) * 16 + (t & 4) * 2, 0.5f * bf_lo(pb), 0.5f * bf_hi(pb));
          }
          __syncwarp();
          if (leader) mbar_arrive(bar(B_EPI1));
          if (bid < 16 && lane < 27) *reinterpret_cast<uint4*>(g_cs + (~ep & 1) * F + bid * 108 + lane * 4) = make_uint4(0, 0, 0, 0);
        }
        asm volatile("barrier.cluster.wait.acquire.aligned;" ::: "memory");
        if (leader) {
          const int b = warp - 1;
          __nv_bfloat16* hrow = g_h + iblk * 54 * 4096;
          unsigned* cnt = &g_cnt[(CNT_H + (iblk * 2 + srank) * 3 + b) * 32];
          mbar_wait(bar(B_HRDY + b), 0);
          if (DL2 && b == 2) mbar_wait(bar(B_FULL + 1 + DL2), 0);
          bulk_store(hrow + (blk1 + b) * 8192, xslot(b == 2 ? 0 : 2 * b + 2), 16384);
          if (b == 2 && has_half) {
            bulk_store(hrow + hb1 * 4096, sb + SPARE + 2 * 16384, 4096);
            bulk_store(hrow + hb1 * 4096 + 2048, sb + SPARE + 3 * 16384, 4096);
          }
          bulk_commit();
          if (RDW) { asm volatile("cp.async.bulk.wait_group.read 0;" ::: "memory"); mbar_arrive(bar(B_STD + b)); }
          bulk_wait<0>();
          red_relaxed(cnt);
          if (!RDW) mbar_arrive(bar(B_STD + b));
          TLREC(32 + b);
          if (b == 2) mbar_arrive_cluster(mapa(bar(B_PEER), srank ^ 1));
          const __nv_bfloat16* src0 = hrow + kblock(26) * 4096;
          if (PRE && b == 0) { mbar_wait(bar(B_EMPTY + 2), 1); mbar_wait(bar(B_EMPTY + 3), 1); }
          poll_acquire(cnt, ep * 4);
          fence_async_all();
          if (PRE && b == 0) {
            bulk_load(sb + 16384, src0, 8192, bar(B_FULL + 2));
            bulk_load(sb + 24576, src0 + 4096, 8192, bar(B_FULL + 3));
          }
          TLREC(35 + b);
          if (b) mbar_wait(bar(B_RDY + b - 1), 0);
          int s = PRE && !b ? 4 : 2, ph = ~b & 1;
#pragma unroll 1
          for (int J = PRE && !b ? 28 : 26 + 6 * b; J < (b == 2 ? 47 : 32 + 6 * b); J++) {
            const __nv_bfloat16* src = hrow + kblock(J) * 4096;
            if (J < 32) mbar_wait(bar(B_STD + ((J - 26) >> 1)), 0);
            mbar_wait(bar(B_EMPTY + s), ph);
            bulk_load(xslot(s) + (s & 1) * 8192, src, 8192, bar(B_FULL + s));
            if (++s == 6) { s = 0; ph ^= 1; }
          }
          mbar_arrive(bar(B_RDY + b));
        }
      }
    } else {
      bar_arrive(6, 288);
      if (DEC) bar_arrive(2, 512);
      asm volatile("barrier.cluster.wait.acquire.aligned;" ::: "memory");
      asm volatile("setmaxnreg.inc.sync.aligned.u32 168;");
      if (!DEC) bar_sync(2, 512);
      const uint32_t flg = sb + FLG + warp * 4;
      const uint64_t dbw = mkdesc(sb + WR, 4096, 1024, 1);
      auto take = [&]() { asm volatile("bar.sync %0, 256;" ::"r"(7 + wg) : "memory"); yield_wait(flg); };
      auto pass = [&]() { asm volatile("bar.arrive %0, 256;" ::"r"(8 - wg) : "memory"); };
      if (DEC < 2 && wg) pass();
      FRESH
      uint32_t pk[56];
      {
        float acc[112];
        int s = 0, ph = 0;
#pragma unroll 1
        for (int kc = 0; kc < 10; kc++) {
          const uint64_t da = mkdesc(xslot(s) + wg * 8192, 16, 1024, 1), db = dbw + s * 1024;
          mbar_wait(bar(B_FULL + s), ph);
          if (wid == 0 && leader) { if (kc == 0 || kc == 2 || kc == 5 || kc == 9) TLREC(50 + kc); TLREC(192 + 2 * kc); }
          if (kc <= 9 - STG) take(); else if (STY) yield_wait(flg);
          wg_fence();
          wgmma_n224(acc, da, db, kc);
          wgmma_n224(acc, da + 2, db + 128, 1);
          wg_commit();
          if (TOK == 0 && (kc < 9 - STG || kc == 9)) pass();
          mbar_wait(bar(B_FULL + s + 1), ph);
          if (wid == 0 && leader) TLREC(193 + 2 * kc);
          wg_fence();
          if (kc == 9) {
            mbar_wait(bar(B_EPI1), 0);
            wg_fence();
            wgmma_ss_bf16_n128k(acc, mkdesc(sb + AT + wg * 1024, 0, 128, 0), mkdesc(sb + BT, 0, 128, 0), 1);
            wgmma_ss_bf16_n96k(acc + 64, mkdesc(sb + AT + wg * 1024, 0, 128, 0), mkdesc(sb + BT + 2048, 0, 128, 0), 1);
            wg_fence();
          }
          wgmma_n224(acc, da + 4, db + 1024, 1);
          if (TOK == 1 && (kc < 9 - STG || kc == 9)) pass();
          wgmma_n224(acc, da + 6, db + 1152, 1);
          wg_commit();
          if (TOK == 2 && (kc < 9 - STG || kc == 9)) pass();
          wg_wait<1>();
          if (leader) mbar_arrive(bar(B_EMPTY + s));
          wg_wait<0>();
          if (leader) mbar_arrive(bar(B_EMPTY + s + 1));
          s += 2;
          if (s == 6) { s = 0; ph ^= 1; }
        }
        reg_pin<112>(acc);
        if (warp == 0 && leader) TLREC(2 + wg * 8);
        const uint2 s0 = lds64(sb + AT + 8 + (wid * 16 + g) * 16), s1 = lds64(sb + AT + 136 + (wid * 16 + g) * 16);
        const float a0 = bf_hi(s0.x) + bf_lo(s0.y), a1 = bf_hi(s1.x) + bf_lo(s1.y);
        auto pack = [&](int i) { const float a = (i & 1) ? a1 : a0; pk[i] = pack_bf16(a * acc[2 * i], a * acc[2 * i + 1]); };
#pragma unroll
        for (int i = 0; i < 4; i++) pack(i);
#pragma unroll
        for (int i = 0; i < 16; i++) {
          pk[i] = gelu2(pk[i]);
          if (i < 13) { pack(4 + 4 * i); pack(5 + 4 * i); pack(6 + 4 * i); pack(7 + 4 * i); }
        }
      }
      float acc[80];
      if (wid == 0 && leader) TLREC(38);
      {
        const uint32_t ho = sb + wg * 4096 + warp * 1024 + ((lane & 15) ^ (srank * 8)) * 64, hx = (lane >> 4) ^ ((lane >> 1) & 3);
        const uint32_t h0 = ho + (hx << 4), h1 = ho + ((hx ^ 2) << 4);
#pragma unroll
        for (int b = 0; b < 3; b++) {
          const int xo = b == 0 ? 16384 : b == 1 ? X2 : 0;
          const uint64_t da = mkdesc(sb + (b == 1 ? 16384 : X2) + wg * 4096, 16, 512, 2), db = dbw + 2 * b * 1024;
          mbar_wait(bar(B_EMPTY + (2 * b + 3) % 6), b == 2);
          if (b) {
            mbar_wait(bar(B_FULL + 2 * b), 1);
            mbar_wait(bar(B_FULL + 2 * b + 1), 1);
            if (b == 2) {
              wg_wait<0>();
              if (leader) { mbar_arrive(bar(B_EMPTY + 2)); mbar_arrive(bar(B_EMPTY + 3)); }
            }
            wg_fence();
          }
#pragma unroll
          for (int n = 0; n < (b == 2 ? 6 : 4); n++) {
            uint32_t* p = pk + b * 16 + n * 4;
            if (b) {
              if (n < 4) wgmma_ss_bf16_n160(acc, da + (n >> 1) * 512 + (n & 1) * 2, db + (n >> 1) * 1024 + (n & 1) * 128, b + n - 1);
              if (n == 3) wg_commit();
              p[0] = gelu2(p[0]); p[1] = gelu2(p[1]); p[2] = gelu2(p[2]); p[3] = gelu2(p[3]);
            }
          }
#pragma unroll
          for (int n = 0; n < (b == 2 ? 6 : 4); n++) {
            const uint32_t* p = pk + b * 16 + n * 4;
            stsm4(((n & 1) ? h1 : h0) + (n < 4 ? xo + (n & 2) * 4096 : SPARE + 2 * 16384 + wg * 12288), p[0], p[1], p[2], p[3]);
          }
          if (wid == 0 && leader) TLREC(b == 0 ? 39 : b == 1 ? 48 : 60);
          fence_async_smem();
          __syncwarp();
          if (leader) mbar_arrive(bar(B_HRDY + b));
          if (wid == 0 && leader) TLREC(b == 0 ? 45 : b == 1 ? 49 : 61);
        }
        wg_wait<0>();
        if (leader) { mbar_arrive(bar(B_EMPTY + 4)); mbar_arrive(bar(B_EMPTY + 5)); }
        if (warp == 0 && leader) TLREC(3 + wg * 8);
      }
      float4 cb[10];
      uint4 xv[5];
      const int ooff = (iblk * 128 + wid * 16 + srank * 8 + g) * D + q * 8;
#pragma unroll
      for (int u = 0; u < 5; u++) if (XVM == 0 && !XT) xv[u] = ldx128(P.x + ooff + (u < 4 ? blk2 * 64 + u * 32 : hb2 * 32));
#pragma unroll
      for (int i = 0; i < 10; i++) if (!CBM) cb[i] = lds128f(sb + EP2 + i * 64 + q * 16);
      if (wid == 0 && leader) TLREC(46);
      {
        int s = 0, ph = 0;
#pragma unroll 1
        for (int m = 2; m < 13; m++) {
          const uint64_t da = mkdesc(xslot(s) + wg * 4096, 16, 512, 2), db = dbw + s * 1024;
          mbar_wait(bar(B_FULL + s), ph);
          if (m == 3 && warp == 0 && leader) TLREC(5 + wg * 8);
          if (m == 2 && wid == 0 && leader) TLREC(47);
          take();
          if (m == 2 && wid == 0 && leader) TLREC(29);
          wg_fence();
          wgmma_ss_bf16_n160(acc, da, db, 1);
          wgmma_ss_bf16_n160(acc, da + 2, db + 128, 1);
          wg_commit();
          if (TOK2 == 0 && m + wg < 13) pass();
          mbar_wait(bar(B_FULL + s + 1), ph);
          if (wid == 0 && leader) TLREC(213 + 2 * m);
          wg_fence();
          if (m == 12) {
            const uint64_t dl = mkdesc(sb + X2 + wg * 4096, 16, 512, 2);
            mbar_wait(bar(B_FULL + 4), 1);
            wg_fence();
#pragma unroll
            for (int u = 0; u < 5; u++) if (XVM == 15) xv[u] = ldx128(P.x + ooff + (u < 4 ? blk2 * 64 + u * 32 : hb2 * 32));
            wgmma_ss_bf16_n160(acc, dl, dbw + 4096, 1);
            wgmma_ss_bf16_n160(acc, dl + 2, dbw + 4096 + 128, 1);
            if (NCL & 1) mbar_wait(bar(B_PEER), 0); else mbar_wait_cl(bar(B_PEER), 0);
            wg_fence();
#pragma unroll
            for (int u = 0; u < 5; u++) if (XVM == 14) xv[u] = ldx128(P.x + ooff + (u < 4 ? blk2 * 64 + u * 32 : hb2 * 32));
          }
          wgmma_ss_bf16_n160(acc, da + 512, db + 1024, 1);
          if (TOK2 == 1 && m + wg < 13) pass();
          wgmma_ss_bf16_n160(acc, da + 514, db + 1152, 1);
          wg_commit();
          if (TOK2 == 2 && m + wg < 13) pass();
          if (XVM && m == XVM) {
#pragma unroll
            for (int u = 0; u < 5; u++) xv[u] = ldx128(P.x + ooff + (u < 4 ? blk2 * 64 + u * 32 : hb2 * 32));
          }
          if (XVM >= 20) {
#pragma unroll
            for (int u = 0; u < 5; u++) if (m == XVM - 20 + (u >> 1) * XST) xv[u] = ldx128(P.x + ooff + (u < 4 ? blk2 * 64 + u * 32 : hb2 * 32));
          }
          if (CBM && m == CBM) {
#pragma unroll
            for (int i = 0; i < 10; i++) cb[i] = lds128f(sb + EP2 + i * 64 + q * 16);
          }
          if (m == 2 && wid == 0 && leader) TLREC(21);
          wg_wait<1>();
          if (leader) mbar_arrive(bar(B_EMPTY + s));
          wg_wait<0>();
          if (leader) mbar_arrive(bar(B_EMPTY + s + 1));
          if (m == 2 && wid == 0 && leader) TLREC(1);
          s += 2;
          if (s == 6) { s = 0; ph ^= 1; }
        }
      }
      reg_pin<80>(acc);
      if (warp == 0 && leader) TLREC(6 + wg * 8);
      constexpr float HS = 0.25f / GS;
      {
        const uint32_t ra = mapa(sb + SPARE + tid * 16, srank ^ 1), rb = mapa(bar(B_XCH + 4 * wg), srank ^ 1), rc = mapa(sb + XB + 16 * wg, srank ^ 1);
        uint32_t sv[20];
#pragma unroll
        for (int i = 0; i < 20; i++) sv[i] = pack_bf16(acc[4 * i + 2], acc[4 * i + 3]);
#pragma unroll
        for (int u = 0; u < 5; u++)
          asm volatile("st.async.weak.shared::cluster.mbarrier::complete_tx::bytes.v4.b32 [%0], {%1,%2,%3,%4}, [%5];"
                       ::"r"(ra + u * 16384), "r"(sv[4 * u]), "r"(sv[4 * u + 1]), "r"(sv[4 * u + 2]), "r"(sv[4 * u + 3]), "r"(u < XC0 ? rb : u < XC1 ? rc : rc + 8) : "memory");
      }
#pragma unroll
      for (int u = 0; u < 5; u++) if (XVM == 13) xv[u] = ldx128(P.x + ooff + (u < 4 ? blk2 * 64 + u * 32 : hb2 * 32));
      if (wid == 0 && leader) TLREC(4);
#pragma unroll
      for (int i = 0; i < 10; i++) {
        float* a = acc + i * 8;
        a[0] = fmaf(HS, a[0], cb[i].x); a[1] = fmaf(HS, a[1], cb[i].y); a[4] = fmaf(HS, a[4], cb[i].z); a[5] = fmaf(HS, a[5], cb[i].w);
      }
      const uint32_t ya = sb + YC + lane * 128 + ((wid ^ (lane & 7)) << 4) - cblk * 5 * 4096;
      const uint32_t xw = sb + SPARE + wid * 512, ta = xw + (lane & 7) * 64 + (((lane >> 3) ^ ((lane >> 1) & 3)) << 4), tb = xw + g * 64 + ((q ^ (lane >> 3)) << 4);
      uint32_t yv[20], o[20];
      uint4 rv[5];
      if (YPRE) {
        mbar_wait(bar(B_YC), 0);
#pragma unroll
        for (int u = 0; u < 5; u++) ldsm4t(ya + (u < 4 ? blk2 * 2 + u : hb2) * 4096, yv[4 * u], yv[4 * u + 1], yv[4 * u + 2], yv[4 * u + 3]);
      }
      if (NCL & 2) mbar_wait(bar(B_XCH + 4 * wg), 0); else mbar_wait_cl(bar(B_XCH + 4 * wg), 0);
      if (warp == 0 && leader) TLREC(7 + wg * 8);
#pragma unroll
      for (int u = 0; u < 5; u++) {
        if (u == XC0 || u == XC1) mbar_wait_cl(sb + XB + 16 * wg + (u == XC1 ? 8 : 0), 0);
        if (u == 0 || u == XC0 || u == XC1) {
#pragma unroll
          for (int v = u; v < (u == 0 ? XC0 : u == XC0 ? XC1 : 5); v++) rv[v] = lds128(xw + v * 16384 + lane * 16);
        }
        const uint32_t r[4] = {rv[u].x, rv[u].y, rv[u].z, rv[u].w};
#pragma unroll
        for (int e = 0; e < 4; e++) {
          const float h0 = fmaf(HS, bf_lo(r[e]), acc[u * 16 + e * 4]), h1 = fmaf(HS, bf_hi(r[e]), acc[u * 16 + e * 4 + 1]);
          o[4 * u + e] = pack_bf16(fmaf(h0, tanh_fast(h0), h0), fmaf(h1, tanh_fast(h1), h1));
        }
      }
      if (!YPRE) mbar_wait(bar(B_YC), 0);
      if (warp == 0 && leader) TLREC(wg ? 12 : 9);
#pragma unroll
      for (int u = 0; u < 5; u++) if (!YPRE) ldsm4t(ya + (u < 4 ? blk2 * 2 + u : hb2) * 4096, yv[4 * u], yv[4 * u + 1], yv[4 * u + 2], yv[4 * u + 3]);
#pragma unroll
      for (int u = 0; u < 5; u++)
        stsm4(ta + u * 16384, bmul2(yv[4 * u], o[4 * u]), bmul2(yv[4 * u + 1], o[4 * u + 1]), bmul2(yv[4 * u + 2], o[4 * u + 2]), bmul2(yv[4 * u + 3], o[4 * u + 3]));
#pragma unroll
      for (int u = 0; u < 5; u++) if (XT) xv[u] = lds128(sb + V5 + u * 4096 + tid * 16);
      __syncwarp();
#pragma unroll
      for (int u = 0; u < 5; u++) rv[u] = lds128(tb + u * 16384);
#pragma unroll
      for (int u = 0; u < 5; u++)
        *reinterpret_cast<uint4*>(P.out + ooff + (u < 4 ? blk2 * 64 + u * 32 : hb2 * 32)) =
            make_uint4(badd2(xv[u].x, rv[u].x), badd2(xv[u].y, rv[u].y), badd2(xv[u].z, rv[u].z), badd2(xv[u].w, rv[u].w));
      if (tid == 0) { red_relaxed(g_epoch + bid); TLGT(63); }
      if (warp == 0 && leader) TLREC(8 + wg * 8);
    }
  }
}

typedef CUresult (*EncodeFn)(CUtensorMap*, CUtensorMapDataType, cuuint32_t, void*, const cuuint64_t*, const cuuint64_t*,
                             const cuuint32_t*, const cuuint32_t*, CUtensorMapInterleave, CUtensorMapSwizzle,
                             CUtensorMapL2promotion, CUtensorMapFloatOOBfill);

struct Dim { cuuint64_t n, stride; cuuint32_t box; };
template <int R>
bool make_map(EncodeFn fn, CUtensorMap* tm, const void* base, const Dim (&d)[R], CUtensorMapSwizzle swz = CU_TENSOR_MAP_SWIZZLE_128B,
              CUtensorMapL2promotion promo = CU_TENSOR_MAP_L2_PROMOTION_L2_128B) {
  cuuint64_t dims[R], strides[R];
  cuuint32_t box[R], es[R];
  for (int i = 0; i < R; i++) { dims[i] = d[i].n; strides[i] = d[i].stride; box[i] = d[i].box; es[i] = 1; }
  return fn(tm, CU_TENSOR_MAP_DATA_TYPE_BFLOAT16, R, const_cast<void*>(base), dims, strides + 1, box, es,
            CU_TENSOR_MAP_INTERLEAVE_NONE, swz, promo, CU_TENSOR_MAP_FLOAT_OOB_FILL_NONE) == CUDA_SUCCESS;
}

}

extern "C" void kernel_launch(void* const* d_in, const int* in_sizes, int n_in, void* d_out, int out_size) {
  static EncodeFn fn = nullptr;
  static void *xt = nullptr, *yc = nullptr;
  static int regs = 0;
  if (!fn) {
    void* p = nullptr;
    cudaDriverEntryPointQueryResult qr;
    cudaGetDriverEntryPoint("cuTensorMapEncodeTiled", &p, cudaEnableDefault, &qr);
    fn = (EncodeFn)p;
    cudaFuncSetAttribute(fused_kernel, cudaFuncAttributeMaxDynamicSharedMemorySize, SMEM_TOTAL + TLX);
    cudaGetSymbolAddress(&xt, g_xnT);
    cudaGetSymbolAddress(&yc, g_yc);
    cudaFuncAttributes fa;
    cudaFuncGetAttributes(&fa, fused_kernel);
    regs = fa.numRegs;
  }
  typedef const __nv_bfloat16* bp;
  Params P{(bp)d_in[0], (bp)d_in[1], (bp)d_in[2], (bp)d_in[3], (bp)d_in[4], (bp)d_in[5], (bp)d_in[6],
           (bp)d_in[8], (bp)d_in[9], (bp)d_in[10], (bp)d_in[11], (__nv_bfloat16*)d_out};
  Maps M;
  bool ok = regs == 128;
  ok &= make_map<2>(fn, &M.x, P.x, {{D, 2, 64}, {L, D * 2, 128}});
  ok &= make_map<3>(fn, &M.w1, P.w1, {{64, 2, 64}, {D, F * 2, 32}, {27, 128, 3}});
  ok &= make_map<2>(fn, &M.w1h, P.w1, {{F, 2, 32}, {D, F * 2, 32}}, CU_TENSOR_MAP_SWIZZLE_128B, CU_TENSOR_MAP_L2_PROMOTION_L2_64B);
  ok &= make_map<3>(fn, &M.w2, P.w2, {{64, 2, 64}, {F, D * 2, 32}, {10, 128, 2}});
  ok &= make_map<2>(fn, &M.w2h, P.w2, {{D, 2, 32}, {F, D * 2, 32}}, CU_TENSOR_MAP_SWIZZLE_128B, CU_TENSOR_MAP_L2_PROMOTION_L2_64B);
  ok &= make_map<2>(fn, &M.xt, xt, {{10240, 2, 16}, {128, 20480, 128}}, CU_TENSOR_MAP_SWIZZLE_32B, CU_TENSOR_MAP_L2_PROMOTION_NONE);
  ok &= make_map<3>(fn, &M.xr, P.x, {{D, 2, 32}, {16, D * 2, 8}, {128, D * 32, 8}}, CU_TENSOR_MAP_SWIZZLE_NONE, CU_TENSOR_MAP_L2_PROMOTION_L2_64B);
  ok &= make_map<2>(fn, &M.yc, yc, {{L, 2, 64}, {D, L * 2, 160}});
  if (ok) fused_kernel<<<128, 512, SMEM_TOTAL + TLX, cudaStreamPerThread>>>(P, M);
}
```
